```python
import torch

def _softmax(x, axis=-1):
    return torch.softmax(x, dim=axis)

def _gelu(x):
    return torch.nn.functional.gelu(x, approximate='tanh')

def _silu(x):
    return torch.nn.functional.silu(x)

def _sigmoid(x):
    return torch.sigmoid(x)

def _layernorm(x, axis=-1, eps=1e-05):
    m = x.mean(dim=axis, keepdim=True)
    v = x.var(dim=axis, keepdim=True, unbiased=False)
    return (x - m) / torch.sqrt(v + eps)

def _scatter_add(tgt, idx, src, axis=0):
    return tgt.clone().index_add_(axis, idx, src)

def _segment_sum(src, seg, n):
    out = torch.zeros((n,) + src.shape[1:], dtype=src.dtype)
    return out.index_add_(0, seg, src)

def _pad(x, pw):
    flat = tuple((v for pair in reversed(pw) for v in pair))
    return torch.nn.functional.pad(x, flat)
kernel_name = 'adaLN_cond__ssm_conv_s4d__geglu_ffn__prompt'

def setup_inputs():

    _w = lambda a: (lambda t: t.to(torch.bfloat16) if t.is_floating_point() else t)(torch.as_tensor(a))

    def _A_setup():
        Bsz, L, D, N = (1, 2048, 640, 128)
        return {'u': _w((lambda *s: torch.randn(*s, dtype=torch.bfloat16) * 0.05)(Bsz, L, D)), 'log_A_real': _w((lambda *s: torch.randn(*s, dtype=torch.bfloat16) * 3.2)(D, N) * 0.5), 'A_imag': _w((lambda *s: torch.randn(*s, dtype=torch.bfloat16) * 0.1)(D, N) * 3.14), 'C_real': _w((lambda *s: torch.randn(*s, dtype=torch.bfloat16) * 0.4)(D, N) / N ** 0.5), 'C_imag': _w((lambda *s: torch.randn(*s, dtype=torch.bfloat16) * 0.4)(D, N) / N ** 0.5), 'log_dt': _w((lambda *s: torch.randn(*s, dtype=torch.bfloat16) * 0.1)(D) * 0.5 - 4.0), 'D_skip': _w((lambda *s: torch.randn(*s, dtype=torch.bfloat16) * 0.1)(D))}
    _A_in = _A_setup()

    def _B_setup():
        B, S, D, F = (1, 2048, 640, 1728)
        return {'x': _w((lambda *s: torch.randn(*s, dtype=torch.bfloat16) * 0.05)(B, S, D)), 'w_gate': _w((lambda *s: torch.randn(*s, dtype=torch.bfloat16) * 0.05)(D, F)), 'w_up': _w((lambda *s: torch.randn(*s, dtype=torch.bfloat16) * 0.05)(D, F)), 'w_down': _w((lambda *s: torch.randn(*s, dtype=torch.bfloat16) * 0.05)(F, D))}
    _B_in = _B_setup()
    return {'A_u': _A_in['u'], 'A_log_A_real': _A_in['log_A_real'], 'A_A_imag': _A_in['A_imag'], 'A_C_real': _A_in['C_real'], 'A_C_imag': _A_in['C_imag'], 'A_log_dt': _A_in['log_dt'], 'A_D_skip': _A_in['D_skip'], 'B_x': _B_in['x'], 'B_w_gate': _B_in['w_gate'], 'B_w_up': _B_in['w_up'], 'B_w_down': _B_in['w_down'], 'c': _w((lambda *s: torch.randn(*s, dtype=torch.bfloat16) * 0.1)(1, 640) * 8.0), 'w_mod': _w((lambda *s: torch.randn(*s, dtype=torch.bfloat16) * 0.1)(640, 6 * 640) * 640 ** (-0.5) * 8.0)}

def reference(A_u, A_log_A_real, A_A_imag, A_C_real, A_C_imag, A_log_dt, A_D_skip, B_x, B_w_gate, B_w_up, B_w_down, c, w_mod):

    def _A_ref(u, log_A_real, A_imag, C_real, C_imag, log_dt, D_skip):
        L = u.shape[1]
        dt = torch.exp(log_dt)
        A = -torch.exp(log_A_real) + 1j * A_imag
        C = (C_real + 1j * C_imag) * dt[:, None]
        pos = (lambda x, dt: x.to(dt))(torch.arange(L), log_dt.dtype)
        P = torch.exp((A * dt[:, None])[:, :, None] * pos[None, None, :])
        K = 2.0 * torch.einsum('dn,dnl->dl', C, P).real
        L2 = 2 * L
        u_t = (lambda x, *d: x.permute(*d))(u, 0, 2, 1)
        Kf = (lambda x, *a, **k: torch.fft.rfft(x.float(), *a, **k))(K, L2)
        Uf = (lambda x, *a, **k: torch.fft.rfft(x.float(), *a, **k))(u_t, L2)
        y = (lambda x, *a, **k: torch.fft.irfft(x, *a, **k).to(torch.bfloat16))(Uf * Kf[None, :, :], L2)[:, :, :L]
        y = (lambda x, *d: x.permute(*d))(y, 0, 2, 1)
        return y + u * D_skip[None, None, :]

    def _B_ref(x, w_gate, w_up, w_down):
        return _gelu(x @ w_gate) * (x @ w_up) @ w_down
    x = A_u
    mod = (_silu(c) @ w_mod).reshape(c.shape[0], 6, 1, -1)
    sa, ca, ga, sb, cb, gb = (mod[:, 0].clone(), mod[:, 1].clone(), mod[:, 2].clone(), mod[:, 3].clone(), mod[:, 4].clone(), mod[:, 5].clone())
    h = _layernorm(x, axis=-1) * (1 + ca) + sa
    x = x + ga * _A_ref(h, A_log_A_real, A_A_imag, A_C_real, A_C_imag, A_log_dt, A_D_skip)
    h = _layernorm(x, axis=-1) * (1 + cb) + sb
    x = x + gb * _B_ref(h, B_w_gate, B_w_up, B_w_down)
    return x
```

```cpp
#include <cuda_runtime.h>
#include <cuda_bf16.h>
#include <cuda_fp16.h>
#include <cuda.h>
#include <stdint.h>

typedef __nv_bfloat16 bf16;
constexpr int L_ = 2048, D_ = 640, N_ = 128, F_ = 1728;

__device__ __forceinline__ uint32_t smem_u32(const void* p){ return (uint32_t)__cvta_generic_to_shared(p); }
__device__ __forceinline__ uint32_t opaque(uint32_t x){ uint32_t y; asm volatile("mov.u32 %0, %1;":"=r"(y):"r"(x)); return y; }
__device__ __forceinline__ uint32_t clk32(){ uint32_t c; asm volatile("mov.u32 %0, %%clock;":"=r"(c)); return c; }
__device__ __forceinline__ bool elect_one(){ uint32_t p; asm volatile("{\n.reg .pred P;\nelect.sync _|P, 0xffffffff;\nselp.u32 %0,1,0,P;\n}":"=r"(p)); return p; }
__device__ __forceinline__ void mbar_init(uint32_t bar, uint32_t cnt){ asm volatile("mbarrier.init.shared::cta.b64 [%0], %1;"::"r"(bar),"r"(cnt):"memory"); }
__device__ __forceinline__ void mbar_expect_tx(uint32_t bar, uint32_t bytes){ asm volatile("mbarrier.arrive.expect_tx.shared::cta.b64 _, [%0], %1;"::"r"(bar),"r"(bytes):"memory"); }
__device__ __forceinline__ void mbar_arrive_pred(uint32_t bar, uint32_t cnt, int pred){
  asm volatile("{\n.reg .pred p;\nsetp.ne.b32 p, %2, 0;\n@p mbarrier.arrive.shared::cta.b64 _, [%0], %1;\n}"::"r"(bar),"r"(cnt),"r"(pred):"memory"); }
__device__ __forceinline__ void mbar_wait(uint32_t bar, uint32_t parity, uint32_t t0){
  asm volatile("{\n.reg .pred p;\n.reg .b32 c;\nLW:\nmbarrier.try_wait.parity.shared::cta.b64 p, [%0], %1;\n@p bra LD;\n"
               "mov.u32 c, %%clock;\nsub.u32 c, c, %2;\nsetp.lt.s32 p, c, 0;\n@p bra LD;\nbra LW;\nLD:\n}"::"r"(bar),"r"(parity),"r"(t0):"memory"); }
__device__ __forceinline__ void flag_wait(const unsigned* f, unsigned target, uint32_t t0){
  asm volatile("{\n.reg .pred p;\n.reg .b32 c;\nLW:\nld.acquire.gpu.global.u32 c, [%0];\nsub.u32 c, c, %1;\nsetp.ge.s32 p, c, 0;\n@p bra LD;\n"
               "mov.u32 c, %%clock;\nsub.u32 c, c, %2;\nsetp.lt.s32 p, c, 0;\n@p bra LD;\nbra LW;\nLD:\n}"::"l"(f),"r"(target),"r"(t0):"memory"); }
__device__ __forceinline__ void red_release(unsigned* f, unsigned v){ asm volatile("red.release.gpu.global.add.u32 [%0], %1;"::"l"(f),"r"(v):"memory"); }
__device__ __forceinline__ unsigned ld_relaxed(const unsigned* f){ unsigned v; asm volatile("ld.relaxed.gpu.global.u32 %0, [%1];":"=r"(v):"l"(f):"memory"); return v; }
__device__ __forceinline__ void fence_async_smem(){ asm volatile("fence.proxy.async.shared::cta;":::"memory"); }
__device__ __forceinline__ void fence_async_all(){ asm volatile("fence.proxy.async;":::"memory"); }
__device__ __forceinline__ void bar_sync(int id, int n){ asm volatile("bar.sync %0, %1;"::"r"(id),"r"(n):"memory"); }
__device__ __forceinline__ void bar_arrive(int id, int n){ asm volatile("bar.arrive %0, %1;"::"r"(id),"r"(n):"memory"); }
__device__ __forceinline__ void bulk_g2s(uint32_t dst, const void* src, uint32_t bytes, uint32_t bar){
  asm volatile("cp.async.bulk.shared::cluster.global.mbarrier::complete_tx::bytes [%0], [%1], %2, [%3];"::"r"(dst),"l"(src),"r"(bytes),"r"(bar):"memory"); }
__device__ __forceinline__ void tma_ld2(uint32_t dst, const CUtensorMap* m, int c0, int c1, uint32_t bar){
  asm volatile("cp.async.bulk.tensor.2d.shared::cluster.global.mbarrier::complete_tx::bytes [%0], [%1, {%3, %4}], [%2];"::"r"(dst),"l"(m),"r"(bar),"r"(c0),"r"(c1):"memory"); }
__device__ __forceinline__ void tma_ld3(uint32_t dst, const CUtensorMap* m, int c0, int c1, int c2, uint32_t bar){
  asm volatile("cp.async.bulk.tensor.3d.shared::cluster.global.mbarrier::complete_tx::bytes [%0], [%1, {%3, %4, %5}], [%2];"::"r"(dst),"l"(m),"r"(bar),"r"(c0),"r"(c1),"r"(c2):"memory"); }
__device__ __forceinline__ void tma_st2(const CUtensorMap* m, int c0, int c1, uint32_t src){
  asm volatile("cp.async.bulk.tensor.2d.global.shared::cta.bulk_group [%0, {%2, %3}], [%1];"::"l"(m),"r"(src),"r"(c0),"r"(c1):"memory"); }
__device__ __forceinline__ void bulk_commit(){ asm volatile("cp.async.bulk.commit_group;":::"memory"); }
__device__ __forceinline__ void bulk_wait0(){ asm volatile("cp.async.bulk.wait_group 0;":::"memory"); }
__device__ __forceinline__ void bulk_wait0_read(){ asm volatile("cp.async.bulk.wait_group.read 0;":::"memory"); }
__device__ __forceinline__ void prefetch_tmap(const CUtensorMap* m){ asm volatile("prefetch.tensormap [%0];"::"l"(m):"memory"); }
__device__ __forceinline__ void wg_fence(){ asm volatile("wgmma.fence.sync.aligned;":::"memory"); }
__device__ __forceinline__ void wg_commit(){ asm volatile("wgmma.commit_group.sync.aligned;":::"memory"); }
template<int N> __device__ __forceinline__ void wg_wait(){ asm volatile("wgmma.wait_group.sync.aligned %0;"::"n"(N):"memory"); }
template<int N> __device__ __forceinline__ void reg_fence(float (&d)[N]){
  #pragma unroll
  for(int i=0;i<N;i++) asm volatile("":"+f"(d[i])::"memory"); }
__device__ __forceinline__ uint64_t mkdesc(uint32_t addr, uint32_t lbo, uint32_t sbo, uint32_t swz){
  return (uint64_t)((addr&0x3FFFF)>>4) | ((uint64_t)(lbo>>4)<<16) | ((uint64_t)(sbo>>4)<<32) | ((uint64_t)swz<<62); }
__device__ __forceinline__ void stsm4(uint32_t a, uint32_t r0, uint32_t r1, uint32_t r2, uint32_t r3){
  asm volatile("stmatrix.sync.aligned.m8n8.x4.shared.b16 [%0], {%1,%2,%3,%4};"::"r"(a),"r"(r0),"r"(r1),"r"(r2),"r"(r3):"memory"); }
__device__ __forceinline__ void stsm4t(uint32_t a, uint32_t r0, uint32_t r1, uint32_t r2, uint32_t r3){
  asm volatile("stmatrix.sync.aligned.m8n8.x4.trans.shared.b16 [%0], {%1,%2,%3,%4};"::"r"(a),"r"(r0),"r"(r1),"r"(r2),"r"(r3):"memory"); }
__device__ __forceinline__ void ldsm4t(uint32_t a, uint32_t& r0, uint32_t& r1, uint32_t& r2, uint32_t& r3){
  asm volatile("ldmatrix.sync.aligned.m8n8.x4.trans.shared.b16 {%0,%1,%2,%3}, [%4];":"=r"(r0),"=r"(r1),"=r"(r2),"=r"(r3):"r"(a):"memory"); }
__device__ __forceinline__ uint4 lds128(uint32_t a){ uint4 v; asm volatile("ld.shared.v4.u32 {%0,%1,%2,%3}, [%4];":"=r"(v.x),"=r"(v.y),"=r"(v.z),"=r"(v.w):"r"(a):"memory"); return v; }
__device__ __forceinline__ float4 lds128f(uint32_t a){ float4 v; asm volatile("ld.shared.v4.f32 {%0,%1,%2,%3}, [%4];":"=f"(v.x),"=f"(v.y),"=f"(v.z),"=f"(v.w):"r"(a):"memory"); return v; }
__device__ __forceinline__ float2 lds64f(uint32_t a){ float2 v; asm volatile("ld.shared.v2.f32 {%0,%1}, [%2];":"=f"(v.x),"=f"(v.y):"r"(a):"memory"); return v; }
__device__ __forceinline__ void sts64f(uint32_t a, float x, float y){ asm volatile("st.shared.v2.f32 [%0], {%1,%2};"::"r"(a),"f"(x),"f"(y):"memory"); }
__device__ __forceinline__ void sts128f(uint32_t a, float4 v){ asm volatile("st.shared.v4.f32 [%0], {%1,%2,%3,%4};"::"r"(a),"f"(v.x),"f"(v.y),"f"(v.z),"f"(v.w):"memory"); }
__device__ __forceinline__ uint32_t pack_bf16(float lo, float hi){ uint32_t r; asm("cvt.rn.bf16x2.f32 %0, %1, %2;":"=r"(r):"f"(hi),"f"(lo)); return r; }
__device__ __forceinline__ float bf_lo(uint32_t v){ return __uint_as_float(v<<16); }
__device__ __forceinline__ float bf_hi(uint32_t v){ return __uint_as_float(v&0xffff0000u); }
__device__ __forceinline__ float tanh_fast(float x){ float y; asm("tanh.approx.f32 %0, %1;":"=f"(y):"f"(x)); return y; }
__device__ __forceinline__ float bfr(float x){ return __bfloat162float(__float2bfloat16_rn(x)); }

__device__ __forceinline__ void wgmma_n144_tt(float (&d)[72], uint64_t da, uint64_t db, int sc){
  asm volatile("{\n.reg .pred p;\nsetp.ne.b32 p, %74, 0;\nwgmma.mma_async.sync.aligned.m64n144k16.f32.bf16.bf16 {%0,%1,%2,%3,%4,%5,%6,%7,%8,%9,%10,%11,%12,%13,%14,%15,%16,%17,%18,%19,%20,%21,%22,%23,%24,%25,%26,%27,%28,%29,%30,%31,%32,%33,%34,%35,%36,%37,%38,%39,%40,%41,%42,%43,%44,%45,%46,%47,%48,%49,%50,%51,%52,%53,%54,%55,%56,%57,%58,%59,%60,%61,%62,%63,%64,%65,%66,%67,%68,%69,%70,%71}, %72, %73, p, 1, 1, 1, 1;\n}\n"
   : "+f"(d[0]),"+f"(d[1]),"+f"(d[2]),"+f"(d[3]),"+f"(d[4]),"+f"(d[5]),"+f"(d[6]),"+f"(d[7]),"+f"(d[8]),"+f"(d[9]),"+f"(d[10]),"+f"(d[11]),"+f"(d[12]),"+f"(d[13]),"+f"(d[14]),"+f"(d[15]),"+f"(d[16]),"+f"(d[17]),"+f"(d[18]),"+f"(d[19]),"+f"(d[20]),"+f"(d[21]),"+f"(d[22]),"+f"(d[23]),"+f"(d[24]),"+f"(d[25]),"+f"(d[26]),"+f"(d[27]),"+f"(d[28]),"+f"(d[29]),"+f"(d[30]),"+f"(d[31]),"+f"(d[32]),"+f"(d[33]),"+f"(d[34]),"+f"(d[35]),"+f"(d[36]),"+f"(d[37]),"+f"(d[38]),"+f"(d[39]),"+f"(d[40]),"+f"(d[41]),"+f"(d[42]),"+f"(d[43]),"+f"(d[44]),"+f"(d[45]),"+f"(d[46]),"+f"(d[47]),"+f"(d[48]),"+f"(d[49]),"+f"(d[50]),"+f"(d[51]),"+f"(d[52]),"+f"(d[53]),"+f"(d[54]),"+f"(d[55]),"+f"(d[56]),"+f"(d[57]),"+f"(d[58]),"+f"(d[59]),"+f"(d[60]),"+f"(d[61]),"+f"(d[62]),"+f"(d[63]),"+f"(d[64]),"+f"(d[65]),"+f"(d[66]),"+f"(d[67]),"+f"(d[68]),"+f"(d[69]),"+f"(d[70]),"+f"(d[71])
   : "l"(da), "l"(db), "r"(sc));
}

__device__ __forceinline__ void wgmma_n80_nt(float (&d)[40], uint64_t da, uint64_t db, int sc){
  asm volatile("{\n.reg .pred p;\nsetp.ne.b32 p, %42, 0;\nwgmma.mma_async.sync.aligned.m64n80k16.f32.bf16.bf16 {%0,%1,%2,%3,%4,%5,%6,%7,%8,%9,%10,%11,%12,%13,%14,%15,%16,%17,%18,%19,%20,%21,%22,%23,%24,%25,%26,%27,%28,%29,%30,%31,%32,%33,%34,%35,%36,%37,%38,%39}, %40, %41, p, 1, 1, 0, 1;\n}\n"
   : "+f"(d[0]),"+f"(d[1]),"+f"(d[2]),"+f"(d[3]),"+f"(d[4]),"+f"(d[5]),"+f"(d[6]),"+f"(d[7]),"+f"(d[8]),"+f"(d[9]),"+f"(d[10]),"+f"(d[11]),"+f"(d[12]),"+f"(d[13]),"+f"(d[14]),"+f"(d[15]),"+f"(d[16]),"+f"(d[17]),"+f"(d[18]),"+f"(d[19]),"+f"(d[20]),"+f"(d[21]),"+f"(d[22]),"+f"(d[23]),"+f"(d[24]),"+f"(d[25]),"+f"(d[26]),"+f"(d[27]),"+f"(d[28]),"+f"(d[29]),"+f"(d[30]),"+f"(d[31]),"+f"(d[32]),"+f"(d[33]),"+f"(d[34]),"+f"(d[35]),"+f"(d[36]),"+f"(d[37]),"+f"(d[38]),"+f"(d[39])
   : "l"(da), "l"(db), "r"(sc));
}

__device__ __forceinline__ void wgmma_n32_rs(float (&d)[16], uint32_t a0, uint32_t a1, uint32_t a2, uint32_t a3, uint64_t db, int sc){
  asm volatile("{\n.reg .pred p;\nsetp.ne.b32 p, %21, 0;\nwgmma.mma_async.sync.aligned.m64n32k16.f32.bf16.bf16 {%0,%1,%2,%3,%4,%5,%6,%7,%8,%9,%10,%11,%12,%13,%14,%15}, {%16,%17,%18,%19}, %20, p, 1, 1, 0;\n}\n"
   : "+f"(d[0]),"+f"(d[1]),"+f"(d[2]),"+f"(d[3]),"+f"(d[4]),"+f"(d[5]),"+f"(d[6]),"+f"(d[7]),"+f"(d[8]),"+f"(d[9]),"+f"(d[10]),"+f"(d[11]),"+f"(d[12]),"+f"(d[13]),"+f"(d[14]),"+f"(d[15])
   : "r"(a0),"r"(a1),"r"(a2),"r"(a3), "l"(db), "r"(sc));
}

__device__ __forceinline__ void wgmma_n24_rs(float (&d)[12], uint32_t a0, uint32_t a1, uint32_t a2, uint32_t a3, uint64_t db, int sc){
  asm volatile("{\n.reg .pred p;\nsetp.ne.b32 p, %17, 0;\nwgmma.mma_async.sync.aligned.m64n24k16.f32.bf16.bf16 {%0,%1,%2,%3,%4,%5,%6,%7,%8,%9,%10,%11}, {%12,%13,%14,%15}, %16, p, 1, 1, 0;\n}\n"
   : "+f"(d[0]),"+f"(d[1]),"+f"(d[2]),"+f"(d[3]),"+f"(d[4]),"+f"(d[5]),"+f"(d[6]),"+f"(d[7]),"+f"(d[8]),"+f"(d[9]),"+f"(d[10]),"+f"(d[11])
   : "r"(a0),"r"(a1),"r"(a2),"r"(a3), "l"(db), "r"(sc));
}

__device__ __forceinline__ void wgmma_n16_tn(float (&d)[8], uint64_t da, uint64_t db, int sc){
  asm volatile("{\n.reg .pred p;\nsetp.ne.b32 p, %10, 0;\nwgmma.mma_async.sync.aligned.m64n16k16.f32.bf16.bf16 {%0,%1,%2,%3,%4,%5,%6,%7}, %8, %9, p, 1, 1, 1, 0;\n}\n"
   : "+f"(d[0]),"+f"(d[1]),"+f"(d[2]),"+f"(d[3]),"+f"(d[4]),"+f"(d[5]),"+f"(d[6]),"+f"(d[7])
   : "l"(da), "l"(db), "r"(sc));
}

__device__ __forceinline__ void ldsm4(uint32_t a, uint32_t& r0, uint32_t& r1, uint32_t& r2, uint32_t& r3){
  asm volatile("ldmatrix.sync.aligned.m8n8.x4.shared.b16 {%0,%1,%2,%3}, [%4];":"=r"(r0),"=r"(r1),"=r"(r2),"=r"(r3):"r"(a):"memory"); }
__device__ __forceinline__ void mma_bf16(float (&d)[4], uint32_t a0,uint32_t a1,uint32_t a2,uint32_t a3,uint32_t b0,uint32_t b1){
  asm("mma.sync.aligned.m16n8k16.row.col.f32.bf16.bf16.f32 {%0,%1,%2,%3},{%4,%5,%6,%7},{%8,%9},{%0,%1,%2,%3};"
   :"+f"(d[0]),"+f"(d[1]),"+f"(d[2]),"+f"(d[3]):"r"(a0),"r"(a1),"r"(a2),"r"(a3),"r"(b0),"r"(b1)); }
__device__ __forceinline__ void mma_f16(float (&d)[4], uint32_t a0,uint32_t a1,uint32_t a2,uint32_t a3,uint32_t b0,uint32_t b1){
  asm("mma.sync.aligned.m16n8k16.row.col.f32.f16.f16.f32 {%0,%1,%2,%3},{%4,%5,%6,%7},{%8,%9},{%0,%1,%2,%3};"
   :"+f"(d[0]),"+f"(d[1]),"+f"(d[2]),"+f"(d[3]):"r"(a0),"r"(a1),"r"(a2),"r"(a3),"r"(b0),"r"(b1)); }
__device__ __forceinline__ uint32_t lds32(uint32_t a){ uint32_t v; asm volatile("ld.shared.u32 %0, [%1];":"=r"(v):"r"(a):"memory"); return v; }
__device__ __forceinline__ float lds32f(uint32_t a){ float v; asm volatile("ld.shared.f32 %0, [%1];":"=f"(v):"r"(a):"memory"); return v; }
__device__ __forceinline__ uint32_t lds16(uint32_t a){ uint32_t v; asm volatile("ld.shared.u16 %0, [%1];":"=r"(v):"r"(a):"memory"); return v; }
__device__ __forceinline__ uint2 lds64(uint32_t a){ uint2 v; asm volatile("ld.shared.v2.u32 {%0,%1}, [%2];":"=r"(v.x),"=r"(v.y):"r"(a):"memory"); return v; }
__device__ __forceinline__ void sts16(uint32_t a, uint32_t v){ asm volatile("st.shared.u16 [%0], %1;"::"r"(a),"h"((unsigned short)v):"memory"); }
__device__ __forceinline__ void sts32(uint32_t a, uint32_t v){ asm volatile("st.shared.u32 [%0], %1;"::"r"(a),"r"(v):"memory"); }
__device__ __forceinline__ void sts32f(uint32_t a, float v){ asm volatile("st.shared.f32 [%0], %1;"::"r"(a),"f"(v):"memory"); }
__device__ __forceinline__ void sts64(uint32_t a, uint32_t x, uint32_t y){ asm volatile("st.shared.v2.u32 [%0], {%1,%2};"::"r"(a),"r"(x),"r"(y):"memory"); }
__device__ __forceinline__ void sts128(uint32_t a, uint32_t x, uint32_t y, uint32_t z, uint32_t w){ asm volatile("st.shared.v4.u32 [%0], {%1,%2,%3,%4};"::"r"(a),"r"(x),"r"(y),"r"(z),"r"(w):"memory"); }
__device__ __forceinline__ uint32_t prmt(uint32_t a, uint32_t b, uint32_t s){ uint32_t r; asm("prmt.b32 %0,%1,%2,%3;":"=r"(r):"r"(a),"r"(b),"r"(s)); return r; }
__device__ __forceinline__ uint32_t pack_h2(float lo, float hi){ uint32_t r; asm("cvt.rn.f16x2.f32 %0, %1, %2;":"=r"(r):"f"(hi),"f"(lo)); return r; }
__device__ __forceinline__ uint32_t bf2_mul(uint32_t a, uint32_t b){ uint32_t r; asm("mul.rn.bf16x2 %0,%1,%2;":"=r"(r):"r"(a),"r"(b)); return r; }
__device__ __forceinline__ uint32_t bf2_add(uint32_t a, uint32_t b){ uint32_t r; asm("add.rn.bf16x2 %0,%1,%2;":"=r"(r):"r"(a),"r"(b)); return r; }
__device__ __forceinline__ uint32_t bf2_fma(uint32_t a, uint32_t b, uint32_t c){ uint32_t r; asm("fma.rn.bf16x2 %0,%1,%2,%3;":"=r"(r):"r"(a),"r"(b),"r"(c)); return r; }
__device__ __forceinline__ uint32_t bf_bits(float x){ return pack_bf16(x,0.f)&0xffffu; }
__device__ __forceinline__ void red_relaxed(unsigned* f){ asm volatile("red.relaxed.gpu.global.add.u32 [%0], 1;"::"l"(f):"memory"); }
__device__ __forceinline__ void fence_async_global(){ asm volatile("fence.proxy.async.global;":::"memory"); }
__device__ __forceinline__ void bulk_s2g(void* dst, uint32_t src, uint32_t bytes){ asm volatile("cp.async.bulk.global.shared::cta.bulk_group [%0], [%1], %2;"::"l"(dst),"r"(src),"r"(bytes):"memory"); }
__device__ __forceinline__ void tma_red2(const CUtensorMap* m, int c0, int c1, uint32_t src){
  asm volatile("cp.reduce.async.bulk.tensor.2d.global.shared::cta.add.bulk_group [%0, {%2, %3}], [%1];"::"l"(m),"r"(src),"r"(c0),"r"(c1):"memory"); }
__device__ __forceinline__ void l2_prefetch(const void* p, uint32_t bytes){ asm volatile("cp.async.bulk.prefetch.L2.global [%0], %1;"::"l"(p),"r"(bytes):"memory"); }
__device__ __forceinline__ uint32_t mod_wait(const unsigned* p, uint32_t tag, uint32_t t0){
  uint32_t v; do{ v=ld_relaxed(p); }while((v&0xffffu)!=tag && (int)(clk32()-t0)>=0); return v&0xffff0000u; }

__device__ __forceinline__ void bar_arrive_pred(int id, int n, int pred){ asm volatile("{\n.reg .pred p;\nsetp.ne.b32 p, %2, 0;\n@p bar.arrive %0, %1;\n}"::"r"(id),"r"(n),"r"(pred):"memory"); }
struct cf { float x, y; };
__device__ __forceinline__ cf csq(cf a){ cf r; r.x=fmaf(a.x,a.x,-a.y*a.y); r.y=(a.x+a.x)*a.y; return r; }
__device__ __forceinline__ cf cmul(cf a, cf b){ cf r; r.x=fmaf(a.x,b.x,-a.y*b.y); r.y=fmaf(a.x,b.y,a.y*b.x); return r; }
__device__ __forceinline__ cf cexp_dir(float l2, float turns){
  float r=(turns-rintf(turns))*6.283185307179586f, m; asm("ex2.approx.f32 %0, %1;":"=f"(m):"f"(l2));
  cf e; e.x=m*__cosf(r); e.y=m*__sinf(r); return e; }
__device__ __forceinline__ void hmulc(uint32_t re, uint32_t im, uint32_t m, uint32_t& ore, uint32_t& oim){
  __half2 R=*(__half2*)&re, I=*(__half2*)&im, M=*(__half2*)&m; __half2 c=__low2half2(M), d=__high2half2(M);
  __half2 a=__hfma2(c,R,__hneg2(__hmul2(d,I))), b=__hfma2(c,I,__hmul2(d,R)); ore=*(uint32_t*)&a; oim=*(uint32_t*)&b; }

__device__ unsigned g_mod[6*D_];
__device__ __align__(1024) bf16 g_inbox[128*128*80];
__device__ __align__(1024) bf16 g_x1T[D_*L_];
__device__ __align__(1024) bf16 g_Wp[D_*2*F_];
__device__ __align__(1024) bf16 g_W2p[F_*D_];
__device__ __align__(1024) bf16 g_G[L_*F_];
__device__ __align__(256) float2 g_qs[2*F_];
__device__ ulonglong2 g_st2[L_];
__device__ unsigned g_cnt[4*32];
__device__ unsigned g_gflag[16*3*32];

constexpr int NSTG = 6, STG = 34816;
constexpr int SM_GS = NSTG*STG, SM_QS = SM_GS+18432, SM_ST = SM_QS+3456, SM_BAR = SM_ST+1024, SM_TOTAL = SM_BAR+256;
constexpr int SM_KG = 0, KG_WG = 28672;
constexpr int SM_TB = 3*KG_WG;
constexpr int SM_XR = SM_TB+5*8192, SM_XS = SM_XR+21504, SM_WM = SM_XS+20480, SM_MI = SM_WM+40960, SM_W2 = SM_MI+6144;
constexpr int PLN = 656, UB = 8*PLN, FPL = 272, FB = 28*FPL;
static_assert(SM_W2+10240 <= SM_QS, "front smem");
static_assert(2*UB+2*FB <= KG_WG, "kg alias");

#define TS(k)
#define TSP(k,p)
constexpr int SM_ALLOC = SM_TOTAL;

struct Params {
  CUtensorMap x1a, x1r, out, xts, xns, x1red, wm, wg, wu, wps, w2l;
  const bf16 *x, *lA, *Ai, *Cr, *Ci, *ldt, *Dsk, *c, *wgp, *wup, *wdp;
  uint32_t zero;
};
__device__ __forceinline__ uint32_t cpz(uint32_t v, uint32_t z){ uint32_t r; asm volatile("xor.b32 %0,%1,%2;":"=r"(r):"r"(v),"r"(z)); return r; }

__device__ __forceinline__ void kgen(uint32_t sb, uint32_t t0, int wg, int warp, int lane, int ch, int d,
                                     uint32_t pa, uint32_t pc, float ldt, float dsk){
  const int tl=warp*32+lane;
  const uint32_t wb=sb+SM_KG+wg*KG_WG+warp*7168;
  const float dt=bfr(expf(ldt));
  const float ar=-bfr(expf(bf_lo(pa)))*dt, ai=bf_hi(pa)*dt;
  const float l2=ar*1.4426950408889634f, tn=ai*0.15915494309189535f;
  uint32_t mx=max(pc&0x7fffu,(pc>>16)&0x7fffu); mx=__reduce_max_sync(~0u,mx);
  uint32_t ex=min(max(mx>>7,1u),253u);
  const float sc=__uint_as_float((254u-ex)<<23), isc=__uint_as_float(ex<<23);
  cf C; C.x=bf_lo(pc)*sc; C.y=bf_hi(pc)*sc;
  const uint32_t sa=wb+lane*16;
  cf E1=cexp_dir(l2,tn), H1=cexp_dir(l2*128.f,tn*128.f);
  cf E2=csq(E1), E3=cmul(E2,E1), E4=csq(E2), E5=cmul(E4,E1), E6=csq(E3), E7=cmul(E4,E3);
  uint32_t r0=pack_h2(1.f,E1.x), r1=pack_h2(E2.x,E3.x), r2=pack_h2(E4.x,E5.x), r3=pack_h2(E6.x,E7.x);
  uint32_t i0=pack_h2(0.f,E1.y), i1=pack_h2(E2.y,E3.y), i2=pack_h2(E4.y,E5.y), i3=pack_h2(E6.y,E7.y);
  sts128(sa+4*512,r0,r1,r2,r3); sts128(sa+5*512,i0,i1,i2,i3);
  { uint32_t m=pack_h2(H1.x,H1.y);
    hmulc(r0,i0,m,r0,i0); hmulc(r1,i1,m,r1,i1); hmulc(r2,i2,m,r2,i2); hmulc(r3,i3,m,r3,i3);
    sts128(sa+6*512,r0,r1,r2,r3); sts128(sa+7*512,i0,i1,i2,i3); }
  const uint32_t m2=pack_h2(E2.x,E2.y), m4=pack_h2(E4.x,E4.y), m6=pack_h2(E6.x,E6.y);
  {
    cf E8=csq(E4); E8.y=-E8.y; cf a0; a0.x=C.x; a0.y=-C.y;
    cf E16=csq(E8), a1=cmul(a0,E8), a2=cmul(a0,E16), a3=cmul(a1,E16), E32=csq(E16), E64=csq(E32);
    r0=pack_h2(a0.x,a1.x); r1=pack_h2(a2.x,a3.x); i0=pack_h2(a0.y,a1.y); i1=pack_h2(a2.y,a3.y);
    uint32_t m=pack_h2(E32.x,E32.y); hmulc(r0,i0,m,r2,i2); hmulc(r1,i1,m,r3,i3);
    sts128(sa,r0,r1,r2,r3); sts128(sa+512,i0,i1,i2,i3);
    m=pack_h2(E64.x,E64.y);
    hmulc(r0,i0,m,r0,i0); hmulc(r1,i1,m,r1,i1); hmulc(r2,i2,m,r2,i2); hmulc(r3,i3,m,r3,i3);
    sts128(sa+2*512,r0,r1,r2,r3); sts128(sa+3*512,i0,i1,i2,i3); }
  float last;
  { cf H2=csq(H1), H3=cmul(H2,H1), H4=csq(H2), H5=cmul(H4,H1), H6=csq(H3), H7=cmul(H4,H3), H8=csq(H4), H16=csq(H8);
    last=fmaf(C.x,H16.x,-C.y*H16.y);
    r0=pack_h2(1.f,H1.x); r1=pack_h2(H2.x,H3.x); r2=pack_h2(H4.x,H5.x); r3=pack_h2(H6.x,H7.x);
    i0=pack_h2(0.f,H1.y); i1=pack_h2(H2.y,H3.y); i2=pack_h2(H4.y,H5.y); i3=pack_h2(H6.y,H7.y);
    uint32_t a,b,c,e,f,g;
    hmulc(r1,i1,m2,a,b); hmulc(r1,i1,m4,c,e); hmulc(r1,i1,m6,f,g);
    sts128(sa+8*512,r1,a,c,f); sts128(sa+9*512,i1,b,e,g);
    hmulc(r2,i2,m4,a,b); hmulc(r3,i3,m4,c,e);
    sts128(sa+10*512,r2,r3,a,c); sts128(sa+11*512,i2,i3,b,e);
    uint32_t m=pack_h2(H8.x,H8.y);
    hmulc(r0,i0,m,r0,i0); hmulc(r1,i1,m,r1,i1); hmulc(r2,i2,m,r2,i2); hmulc(r3,i3,m,r3,i3);
    sts128(sa+12*512,r0,r1,r2,r3); sts128(sa+13*512,i0,i1,i2,i3); }
  #pragma unroll
  for(int o=16;o;o>>=1) last+=__shfl_xor_sync(~0u,last,o);
  __syncwarp();
  float acc[5][4];
  #pragma unroll
  for(int i=0;i<5;i++){ acc[i][0]=0; acc[i][1]=0; acc[i][2]=0; acc[i][3]=0; }
  { const int mi=lane>>3;
    const uint32_t aA=wb+(((mi&1)*2+(mi>>1))*512)+(lane&7)*16;
    const uint32_t aB=wb+4*512+mi*512+(lane&7)*16;
    const uint32_t aC=wb+(12+(mi&1))*512+(mi>>1)*128+(lane&7)*16;
    #pragma unroll
    for(int op=0;op<2;op++){
      uint32_t c0,c1,c2,c3; ldsm4t(aC+op*256,c0,c1,c2,c3);
      #pragma unroll
      for(int oo=0;oo<2;oo++){
        const int o=op*2+oo; uint32_t a0,a1,a2,a3,b0,b1,b2,b3,b4,b5,b6,b7;
        ldsm4t(aA+o*128,a0,a1,a2,a3); ldsm4t(aB+o*128,b0,b1,b2,b3); ldsm4t(aB+2048+o*128,b4,b5,b6,b7);
        mma_f16(acc[0],a0,a1,a2,a3,b0,b1); mma_f16(acc[1],a0,a1,a2,a3,b2,b3);
        mma_f16(acc[2],a0,a1,a2,a3,b4,b5); mma_f16(acc[3],a0,a1,a2,a3,b6,b7);
        mma_f16(acc[4],a0,a1,a2,a3,oo?c2:c0,oo?c3:c1);
      }
    } }
  __syncwarp();
  const float os=2.f*dt*isc;
  #pragma unroll
  for(int i=0;i<5;i++) sts128f(wb+i*512+lane*16, make_float4(acc[i][0]*os,acc[i][1]*os,acc[i][2]*os,acc[i][3]*os));
  if(lane==0) sts32f(wb+2560,last*os);
  bar_sync(1+wg,128);
  const uint32_t w0=sb+SM_KG+wg*KG_WG, ft=w0+4096+2;
  { const int g=tl>>4, t=(tl>>2)&3, e=tl&1, row=g+(tl&2)*4;
    int idx[5]={8*row+2*t+e, 128+8*row+2*t+e, 256+64*e+t+4*row, 384+64*(t&1)+32*e+(t>>1)+2*row, 512+32*t+16*e+row};
    #pragma unroll
    for(int i=0;i<5;i++){
      float s=(lds32f(w0+i*512+tl*4)+lds32f(w0+7168+i*512+tl*4))+(lds32f(w0+2*7168+i*512+tl*4)+lds32f(w0+3*7168+i*512+tl*4));
      if(i==0 && tl==0) s+=dsk;
      sts16(ft+idx[i]*2,bf_bits(s));
    }
    if(tl==127){ float s=(lds32f(w0+2560)+lds32f(w0+7168+2560))+(lds32f(w0+2*7168+2560)+lds32f(w0+3*7168+2560));
      sts16(ft+640*2,bf_bits(s)); sts16(ft-2,0); } }
  bar_sync(1+wg,128);
  const uint32_t P=sb+SM_TB+ch*8192+256, T3=sb+SM_TB+ch*8192+4736;
  { const uint32_t fa=ft+tl*2; const bool ev=!(tl&1);
    sts32(P+tl*4, lds16(fa)|(lds16(fa-2)<<16));
    sts32(P+512+tl*4, lds16(fa+256)|(lds16(fa+254)<<16));
    uint32_t f=lds16(fa+512), fm=lds16(fa+510), fp=lds16(fa+514);
    uint32_t km=(ev && tl)?f:fm, kp=ev?f:fp;
    sts64(P+1024+tl*8, f|(km<<16), kp|(f<<16));
    f=lds16(fa+768); fp=lds16(fa+770); uint32_t k2=ev?f:fp, ff=f|(f<<16);
    sts128(P+2048+tl*16, ff, ff, k2|(f<<16), fp|(k2<<16));
    f=lds16(ft+1024);
    if(tl<96) sts32(P+4096+tl*4, tl<5? (f|(f<<16)) : (tl==5? f<<16 : 0u));
    if(tl<64){ sts32(P-256+tl*4,0); sts128(T3+(tl>>3)*384+256+(tl&7)*16,0,0,0,0); }
    const int z0=(tl&7)+8-(tl&8); const uint32_t ta=ft+(512+(tl>>4)+1+8*z0)*2;
    uint32_t v[8];
    #pragma unroll
    for(int k=0;k<8;k++){ v[k]=lds16(ta-16*k); if(z0<k) v[k]=0; }
    sts128(T3+(tl>>4)*384+(tl&15)*16, v[0]|(v[1]<<16), v[2]|(v[3]<<16), v[4]|(v[5]<<16), v[6]|(v[7]<<16));
  }
  bar_sync(1+wg,128);
}

__global__ void __launch_bounds__(512,1) fused_kernel(const __grid_constant__ Params p){
  extern __shared__ __align__(1024) unsigned char smem[];
  const uint32_t sb = opaque(smem_u32(smem));
  const uint32_t t0 = clk32();
  const int tid=threadIdx.x, lane=tid&31, tl=tid&127;
  const int wid=__shfl_sync(~0u,tid>>5,0), wg=wid>>2, warp=wid&3;
  const int cta=blockIdx.x, m=cta>>3, j=cta&7;
  const int g=lane>>2, t=lane&3;
  const int lead = tl==0;
  const uint32_t fullb=sb+SM_BAR, emptyb=fullb+64, gsb=fullb+128, depb=fullb+136, xb=fullb+168, wmb=fullb+176, w1b=fullb+184, w2b=fullb+192;
  const unsigned cnt0=ld_relaxed(g_cnt);
  if(wg<3){
    const int nch = wg<2 ? 2 : 1;
    uint32_t pa[2], pc[2]; float ldt[2], dsk[2];
    #pragma unroll
    for(int r=0;r<2;r++){ int d=5*cta+min(wg+3*r,4); int o=d*N_+tl;
      pa[r]=(uint32_t)__ldg((const unsigned short*)p.lA+o)|((uint32_t)__ldg((const unsigned short*)p.Ai+o)<<16);
      pc[r]=(uint32_t)__ldg((const unsigned short*)p.Cr+o)|((uint32_t)__ldg((const unsigned short*)p.Ci+o)<<16);
      ldt[r]=__bfloat162float(p.ldt[d]); dsk[r]=__bfloat162float(p.Dsk[d]); }
    TSP(1,tid==0 && pa[0]!=0x12345);
    #pragma unroll 1
    for(int r=0;r<nch;r++){ kgen(sb,t0,wg,warp,lane,wg+3*r,5*cta+wg+3*r, r?pa[1]:pa[0], r?pc[1]:pc[0], r?ldt[1]:ldt[0], r?dsk[1]:dsk[0]); TSP(2+r,tid==0); }
    const unsigned ep=cnt0>>9; const uint32_t tag16=ep%65535u+1, tg2=ep%3u+1, TG=((tg2&1)<<14)|((tg2>>1)<<30);
    const uint32_t kb=sb+SM_KG+wg*KG_WG;
    if(tl<72){ uint32_t a=kb+(tl/9)*PLN+(tl%9)*16; sts128(a,0,0,0,0); sts128(a+UB,0,0,0,0); }
    else if(tl<72+28){ uint32_t a=kb+2*UB+(tl-72)*FPL; sts128(a,0,0,0,0); sts128(a+FB,0,0,0,0); }
    #pragma unroll 1
    for(int r=0;r<nch;r++){
      const int ch=wg+3*r, d=5*cta+ch;
      const uint32_t U=kb+r*UB, Fb=kb+2*UB+r*FB;
      { const uint4* src=(const uint4*)(g_inbox+(size_t)cta*128*80+(tl>>1)*80+ch*16+(tl&1)*8);
        uint4 v[2];
        #pragma unroll
        for(int q=0;q<2;q++){
          do{ asm volatile("ld.relaxed.gpu.global.v4.u32 {%0,%1,%2,%3}, [%4];":"=r"(v[q].x),"=r"(v[q].y),"=r"(v[q].z),"=r"(v[q].w):"l"(src+q*640):"memory");
              v[q].x^=TG; v[q].y^=TG; v[q].z^=TG; v[q].w^=TG;
          }while(((v[q].x|v[q].y|v[q].z|v[q].w)&0x40004000u) && (int)(clk32()-t0)>=0); }
        TSP(4+4*r,tid==0);
        uint32_t sa=mod_wait(g_mod+d,tag16,t0), ca=mod_wait(g_mod+D_+d,tag16,t0);
        sa|=sa>>16; float cs=bfr(1.f+__uint_as_float(ca))*4294967296.f; uint32_t c2=pack_bf16(cs,cs);
        #pragma unroll
        for(int q=0;q<2;q++) sts128(U+(tl&7)*PLN+(9+16*q+(tl>>3))*16, bf2_add(bf2_mul(v[q].x,c2),sa), bf2_add(bf2_mul(v[q].y,c2),sa), bf2_add(bf2_mul(v[q].z,c2),sa), bf2_add(bf2_mul(v[q].w,c2),sa));
      }
      bar_sync(1+wg,128);
      { const int q0=tl+6, q1=tl+7, q2=tl+8;
        uint2 lo=lds64(U+(q0&7)*PLN+(8+(q0>>3))*16+8); uint4 mid=lds128(U+(q1&7)*PLN+(8+(q1>>3))*16); uint2 hi=lds64(U+(q2&7)*PLN+(8+(q2>>3))*16);
        uint32_t w[8]={lo.x,lo.y,mid.x,mid.y,mid.z,mid.w,hi.x,hi.y}; float u[16];
        #pragma unroll
        for(int i=0;i<8;i++){ u[2*i]=bf_lo(w[i]); u[2*i+1]=bf_hi(w[i]); }
        float s7[8], s9[8];
        s7[0]=((u[1]+u[2])+(u[3]+u[4]))+((u[5]+u[6])+u[7]);
        #pragma unroll
        for(int i=1;i<8;i++) s7[i]=s7[i-1]+(u[i+7]-u[i]);
        #pragma unroll
        for(int i=0;i<8;i++) s9[i]=s7[i]+(u[i]+u[i+8]);
        const int ph=q1&7, aa=q1>>3;
        uint32_t a0=pack_bf16(s9[0],s9[1]),a1=pack_bf16(s9[2],s9[3]),a2=pack_bf16(s9[4],s9[5]),a3=pack_bf16(s9[6],s9[7]);
        if(aa<16) sts128(Fb+ph*FPL+aa*16,a0,a1,a2,a3);
        if(aa>0 && ph<6) sts128(Fb+(ph+8)*FPL+(aa-1)*16,a0,a1,a2,a3);
        a0=pack_bf16(s7[0],s7[1]);a1=pack_bf16(s7[2],s7[3]);a2=pack_bf16(s7[4],s7[5]);a3=pack_bf16(s7[6],s7[7]);
        if(aa<16 && ph>0) sts128(Fb+(14+ph-1)*FPL+aa*16,a0,a1,a2,a3);
        if(aa>0 && ph<7) sts128(Fb+(14+ph+7)*FPL+(aa-1)*16,a0,a1,a2,a3);
      }
      fence_async_smem();
      bar_sync(1+wg,128);
      TSP(5+4*r,tid==0);
      float c32[16], c24[12], c16[8];
      { const uint32_t T3=sb+SM_TB+ch*8192+4736;
        wg_fence();
        #pragma unroll
        for(int c=1;c<=8;c++) wgmma_n16_tn(c16, mkdesc(Fb+((c&1)?(14+7-c):(8-c))*FPL,128,FPL,0), mkdesc(T3+(c-1)*384,128,128,0), c>1);
        wg_commit(); }
      uint32_t pp=sb+SM_TB+ch*8192+256+(16*warp+g-2*t-48)*4;
      uint32_t vm=lds32(pp-32); const uint32_t zr=p.zero;
      uint64_t db=mkdesc(U+9*16,PLN,128,0);
      #pragma unroll 1
      for(int dl=0;dl<8;dl++){
        uint32_t v[8];
        #pragma unroll
        for(int i=0;i<8;i++) v[i]=lds32(pp+i*32);
        wg_wait<0>();
        uint32_t a[16];
        #pragma unroll
        for(int i=0;i<4;i++){ a[4*i]=cpz(v[2*i],zr); a[4*i+1]=cpz(v[2*i+1],zr); a[4*i+2]=cpz(i?v[2*i-1]:vm,zr); a[4*i+3]=cpz(v[2*i],zr); }
        wg_fence();
        wgmma_n32_rs(c32, a[0],a[1],a[2],a[3], db+6*(PLN/16), dl>0);
        wgmma_n32_rs(c32, a[4],a[5],a[6],a[7], db+4*(PLN/16), 1);
        wgmma_n32_rs(c32, a[8],a[9],a[10],a[11], db+2*(PLN/16), 1);
        wgmma_n32_rs(c32, a[12],a[13],a[14],a[15], db, 1);
        wg_commit();
        vm=v[7]; pp+=256; db-=1;
      }
      db+=8;
      #pragma unroll 1
      for(int dl=8;dl<17;dl++){
        uint32_t v[8];
        #pragma unroll
        for(int i=0;i<8;i++) v[i]=lds32(pp+i*32);
        wg_wait<0>();
        uint32_t a[16];
        #pragma unroll
        for(int i=0;i<4;i++){ a[4*i]=cpz(v[2*i],zr); a[4*i+1]=cpz(v[2*i+1],zr); a[4*i+2]=cpz(i?v[2*i-1]:vm,zr); a[4*i+3]=cpz(v[2*i],zr); }
        wg_fence();
        wgmma_n24_rs(c24, a[0],a[1],a[2],a[3], db+6*(PLN/16), dl>8);
        wgmma_n24_rs(c24, a[4],a[5],a[6],a[7], db+4*(PLN/16), 1);
        wgmma_n24_rs(c24, a[8],a[9],a[10],a[11], db+2*(PLN/16), 1);
        wgmma_n24_rs(c24, a[12],a[13],a[14],a[15], db, 1);
        wg_commit();
        vm=v[7]; pp+=256; db-=1;
      }
      { uint32_t v0=lds32(pp), v1=lds32(pp+32);
        wg_wait<0>();
        uint32_t a0=cpz(v0,zr), a1=cpz(v1,zr), a2=cpz(vm,zr), a3=cpz(v0,zr);
        wg_fence();
        wgmma_n24_rs(c24, a0,a1,a2,a3, db+6*(PLN/16), 1);
        wg_commit(); }
      const float ga=__uint_as_float(mod_wait(g_mod+2*D_+d,tag16,t0));
      wg_wait<0>();
      reg_fence(c32); reg_fence(c24); reg_fence(c16);
      TSP(6+4*r,tid==0);
      bar_sync(1+wg,128);
      { const uint32_t stg=sb+SM_TB+ch*8192;
        uint32_t o[8];
        #pragma unroll
        for(int i=0;i<8;i++){
          float y0=c32[2*i], y1=c32[2*i+1];
          if(i>=2){ y0+=c24[2*i-4]; y1+=c24[2*i-3]; }
          if(i>=6){ y0+=c16[2*i-12]; y1+=c16[2*i-11]; } else if(i>=4){ y0+=c16[2*i-4]; y1+=c16[2*i-3]; }
          uint32_t yb=pack_bf16(y0,y1);
          o[i]=pack_bf16(ga*bf_lo(yb), ga*bf_hi(yb));
        }
        const uint32_t a=stg+((lane>>4)*8+(lane&7))*128+(((2*warp+((lane>>3)&1))^(lane&7))<<4);
        stsm4t(a,o[0],o[1],o[2],o[3]); stsm4t(a+2048,o[4],o[5],o[6],o[7]);
        fence_async_smem();
        bar_sync(1+wg,128);
        if(warp==0){ if(elect_one()){
          if(r==0){ flag_wait(g_cnt+32,(ep+1)*128,t0); fence_async_global(); }
          tma_red2(&p.x1red,0,d*32,stg); bulk_commit();
          if(r==nch-1){ bulk_wait0(); red_relaxed(g_cnt); } }
          __syncwarp(); }
      }
      TSP(7+4*r,tid==0);
    }
    if(wg==2 && warp==1){
      if(elect_one()){
        if(cta<108){
          #pragma unroll 1
          for(int b=0;b<2;b++){ int bl=cta*2+b, jj=bl/27, kc=bl%27;
            mbar_expect_tx(w2b,10240); tma_ld3(sb+SM_W2,&p.w2l,0,kc*64,jj*5,w2b); mbar_wait(w2b,b,t0);
            bulk_s2g((unsigned char*)g_W2p+(size_t)bl*10240,sb+SM_W2,10240); bulk_commit(); if(b==0) bulk_wait0_read(); }
          bulk_wait0(); }
        red_relaxed(g_cnt+64);
      }
      __syncwarp();
    }
  } else {
    const uint32_t MI=sb+SM_MI;
    if(warp==0){ if(elect_one()){
      for(int i=0;i<NSTG;i++){ mbar_init(fullb+8*i,1); mbar_init(emptyb+8*i,1); }
      mbar_init(gsb,1); for(int i=0;i<4;i++) mbar_init(depb+8*i,1);
      mbar_init(xb,1); mbar_init(wmb,1); mbar_init(w1b,1); mbar_init(w2b,1);
      fence_async_smem();
      mbar_expect_tx(xb,20480);
      #pragma unroll 1
      for(int i=0;i<16;i++) bulk_g2s(sb+SM_XR+i*1296,p.x+(size_t)(cta*16+i)*D_,1280,xb);
      prefetch_tmap(&p.wm); prefetch_tmap(&p.xns); prefetch_tmap(&p.xts);
      } __syncwarp(); }
    #pragma unroll
    for(int i=0;i<5;i++){ float x=__bfloat162float(p.c[tl+128*i]); sts16(MI+(tl+128*i)*2, bf_bits(x/(1.f+__expf(-x)))); }
    bar_sync(4,128);
    if(warp==0 && cta<120){ if(elect_one()){
      mbar_expect_tx(wmb,40960);
      #pragma unroll 1
      for(int i=0;i<4;i++) tma_ld2(sb+SM_WM+i*10240,&p.wm,cta*32,i*160,wmb);
      } __syncwarp(); }
    const unsigned ep=cnt0>>9; const uint32_t tag16=ep%65535u+1, tg2=ep%3u+1, TG=((tg2&1)<<14)|((tg2>>1)<<30);
    TSP(12,lead);
    mbar_wait(xb,0,t0);
    TSP(13,lead);
    {
      const uint32_t xa=sb+SM_XR+(lane&15)*1296+(warp*160+(lane>>4)*8)*2;
      float c1[4]={0,0,0,0}, c2[4]={0,0,0,0}, c3[4]={0,0,0,0};
      #pragma unroll
      for(int k=0;k<10;k++){ uint32_t a0,a1,a2,a3; ldsm4(xa+k*32,a0,a1,a2,a3);
        mma_bf16(c1,a0,a1,a2,a3,a0,a2); mma_bf16(c2,a0,a1,a2,a3,a1,a3); mma_bf16(c3,a0,a1,a2,a3,0x3f803f80u,0x3f803f80u); }
      if(t==(g>>1)){ uint32_t a=MI+3840+warp*128+g*8; sts64f(a,c3[0],(g&1)?c1[1]:c1[0]); sts64f(a+64,c3[2],(g&1)?c2[3]:c2[2]); }
      uint32_t xv[40];
      #pragma unroll
      for(int k=0;k<10;k++) ldsm4t(xa+k*32,xv[4*k],xv[4*k+1],xv[4*k+2],xv[4*k+3]);
      bar_sync(4,128);
      float su=0,sq=0;
      #pragma unroll
      for(int w=0;w<4;w++){ float2 q=lds64f(MI+3840+w*128+(lane&15)*8); su+=q.x; sq+=q.y; }
      const float mu=su*(1.f/D_), var=bfr(fmaxf(sq*(1.f/D_)-mu*mu,0.f));
      const float rr=2.3283064365386963e-10f/bfr(sqrtf(bfr(var+1e-5f))), rh=bfr(rr);
      const uint32_t w1=pack_bf16(-mu,rh), w2=bf_bits(rr-rh);
      uint32_t nm[2], r2h[2], r2l[2];
      #pragma unroll
      for(int h=0;h<2;h++){ uint32_t a=__shfl_sync(~0u,w1,8*h+2*t), b=__shfl_sync(~0u,w1,8*h+2*t+1), c=__shfl_sync(~0u,w2,8*h+2*t), e=__shfl_sync(~0u,w2,8*h+2*t+1);
        nm[h]=prmt(a,b,0x5410); r2h[h]=prmt(a,b,0x7632); r2l[h]=prmt(c,e,0x5410); }
      const int chl=warp*160+(lane>>4)*8+(lane&7), hh=(lane>>3)&1;
      const uint32_t na=sb+SM_XR+chl*32+hh*16, ra=sb+SM_XS+chl*32+((hh^((chl>>2)&1))<<4);
      #pragma unroll
      for(int k=0;k<10;k++){ uint32_t o[4];
        #pragma unroll
        for(int i=0;i<4;i++){ uint32_t dd=bf2_add(xv[4*k+i],nm[i&1]); o[i]=bf2_fma(dd,r2h[i&1],bf2_mul(dd,r2l[i&1]))|TG; }
        stsm4(na+k*512,o[0],o[1],o[2],o[3]); }
      fence_async_smem();
      bar_sync(4,128);
      if(warp==0){ if(elect_one()){ tma_st2(&p.xns,cta*80,0,sb+SM_XR); bulk_commit(); } __syncwarp(); }
      TSP(14,lead);
      #pragma unroll
      for(int k=0;k<10;k++) stsm4(ra+k*512,xv[4*k],xv[4*k+1],xv[4*k+2],xv[4*k+3]);
      fence_async_smem();
      bar_sync(4,128);
      if(warp==0){ if(elect_one()){
        #pragma unroll 1
        for(int i=0;i<4;i++) tma_st2(&p.xts,cta*16,i*160,sb+SM_XS+i*5120);
        bulk_commit();
        l2_prefetch((const unsigned char*)p.wgp+(size_t)cta*17280,17280); l2_prefetch((const unsigned char*)p.wup+(size_t)cta*17280,17280);
        l2_prefetch((const unsigned char*)p.wdp+(size_t)cta*17280,17280);
        } __syncwarp(); }
    }
    const int mi=lane>>3;
    const uint32_t toff=warp*10240+((mi>>1)*8+(lane&7))*64, tsw=(lane>>1)&3;
    if(cta<120){
      mbar_wait(wmb,0,t0);
      TSP(15,lead);
      float c0[4]={0,0,0,0}, c1[4]={0,0,0,0};
      #pragma unroll
      for(int k=0;k<10;k++){ uint32_t b0=lds32(MI+(warp*160+k*16+2*t)*2), b1=lds32(MI+(warp*160+k*16+8+2*t)*2), a0,a1,a2,a3;
        ldsm4t(sb+SM_WM+toff+k*1024+(((mi&1)^tsw)<<4),a0,a1,a2,a3); mma_bf16(c0,a0,a1,a2,a3,b0,b1);
        ldsm4t(sb+SM_WM+toff+k*1024+(((2+(mi&1))^tsw)<<4),a0,a1,a2,a3); mma_bf16(c1,a0,a1,a2,a3,b0,b1); }
      if(t==0){ uint32_t a=MI+3840+512+warp*128+g*4; sts32f(a,c0[0]); sts32f(a+32,c0[2]); sts32f(a+64,c1[0]); sts32f(a+96,c1[2]); }
      bar_sync(4,128);
      if(warp==0){ uint32_t a=MI+3840+512+lane*4; float s=(lds32f(a)+lds32f(a+128))+(lds32f(a+256)+lds32f(a+384));
        asm volatile("st.relaxed.gpu.global.u32 [%0], %1;"::"l"(g_mod+cta*32+lane),"r"((bf_bits(s)<<16)|tag16):"memory"); }
      TSP(16,lead);
    }
    const int mat=cta>=54, sl=cta-54*mat;
    if(warp==0){ if(elect_one()){
      bulk_wait0(); red_relaxed(g_cnt+32);
      if(cta<108){ mbar_expect_tx(w1b,40960);
        #pragma unroll 1
        for(int i=0;i<4;i++) tma_ld2(sb+SM_XR+i*10240,mat?&p.wu:&p.wg,sl*32,i*160,w1b); }
      } __syncwarp(); }
    TSP(17,lead);
    if(cta<108){
      #pragma unroll
      for(int i=0;i<5;i++){ int d=tl+128*i; uint32_t s=mod_wait(g_mod+3*D_+d,tag16,t0), c=mod_wait(g_mod+4*D_+d,tag16,t0);
        sts16(MI+2560+d*2,s>>16); sts16(MI+1280+d*2,bf_bits(1.f+__uint_as_float(c))); }
      bar_sync(4,128);
      TSP(18,lead);
      mbar_wait(w1b,0,t0);
      TSP(19,lead);
      float q0[4]={0,0,0,0}, q1[4]={0,0,0,0}, s0[4]={0,0,0,0}, s1[4]={0,0,0,0};
      const uint32_t oa=sb+SM_WM+(mi&1)*10240+(warp*20+(mi>>1))*128+(lane&7)*16;
      #pragma unroll
      for(int k=0;k<10;k++){ const uint32_t va=MI+(warp*160+k*16+2*t)*2;
        uint32_t c0=lds32(va+1280), c1=lds32(va+1296), b0=lds32(va+2560), b1=lds32(va+2576), a0,a1,a2,a3;
        ldsm4t(sb+SM_XR+toff+k*1024+(((mi&1)^tsw)<<4),a0,a1,a2,a3); mma_bf16(s0,a0,a1,a2,a3,b0,b1);
        a0=bf2_mul(a0,c0); a1=bf2_mul(a1,c0); a2=bf2_mul(a2,c1); a3=bf2_mul(a3,c1);
        mma_bf16(q0,a0,a1,a2,a3,0x3f803f80u,0x3f803f80u); stsm4t(oa+k*256,a0,a1,a2,a3);
        ldsm4t(sb+SM_XR+toff+k*1024+(((2+(mi&1))^tsw)<<4),a0,a1,a2,a3); mma_bf16(s1,a0,a1,a2,a3,b0,b1);
        a0=bf2_mul(a0,c0); a1=bf2_mul(a1,c0); a2=bf2_mul(a2,c1); a3=bf2_mul(a3,c1);
        mma_bf16(q1,a0,a1,a2,a3,0x3f803f80u,0x3f803f80u); stsm4t(oa+20480+k*256,a0,a1,a2,a3); }
      if(t==0){ uint32_t a=MI+3840+warp*256+g*8; sts64f(a,q0[0],s0[0]); sts64f(a+64,q0[2],s0[2]); sts64f(a+128,q1[0],s1[0]); sts64f(a+192,q1[2],s1[2]); }
      fence_async_smem();
      bar_sync(4,128);
      if(warp==0){
        float2 a=lds64f(MI+3840+lane*8), b=lds64f(MI+3840+256+lane*8), c=lds64f(MI+3840+512+lane*8), e=lds64f(MI+3840+768+lane*8);
        const float hs=mat?0.5f:1.f;
        sts64f(MI+4864+lane*8, hs*((a.x+b.x)+(c.x+e.x)), hs*((a.y+b.y)+(c.y+e.y)));
        fence_async_smem(); __syncwarp();
        if(elect_one()){
          #pragma unroll 1
          for(int i=0;i<4;i++){ int pc=sl*4+i, s=pc/72, jj=(pc%72)/9, ii=pc%9; tma_st2(&p.wps,(2*ii+mat)*64,(jj*3+s)*80,sb+SM_WM+i*10240); }
          bulk_s2g(g_qs+mat*F_+sl*32,MI+4864,256);
          bulk_commit(); bulk_wait0(); }
        __syncwarp(); }
    }
    if(lead) red_relaxed(g_cnt);
    TSP(20,lead);
  }
  __syncthreads();
  if(wg>=2){
    asm volatile("setmaxnreg.dec.sync.aligned.u32 48;");
    const unsigned ep=cnt0>>9;
    if(wid==8){ if(elect_one()){
      const unsigned char* wp=(const unsigned char*)g_Wp + (size_t)j*30*18432;
      TS(21);
      flag_wait(g_cnt,(ep+1)*512,t0); fence_async_global();
      TS(22);
      int s=0, ph=1; int kc=0;
      #pragma unroll 1
      for(int i=0;i<30;i++){
        mbar_wait(emptyb+8*s,ph,t0);
        uint32_t st=sb+s*STG, fb=fullb+8*s;
        mbar_expect_tx(fb,STG);
        tma_ld2(st,&p.x1a,m*128,kc*64,fb);
        tma_ld2(st+8192,&p.x1a,m*128+64,kc*64,fb);
        bulk_g2s(st+16384,wp,18432,fb);
        wp+=18432; if(++kc==10) kc=0;
        if(++s==NSTG){s=0;ph^=1;}
      }
      { mbar_wait(emptyb+8*s,ph,t0);
        uint32_t st=sb+s*STG, fb=fullb+8*s;
        mbar_expect_tx(fb,20480);
        tma_ld2(st,&p.x1r,m*128,j*80,fb);
        tma_ld2(st+10240,&p.x1r,m*128+64,j*80,fb);
        if(++s==NSTG){s=0;ph^=1;} }
      const unsigned char* gp=(const unsigned char*)g_G+(size_t)m*27*16384; const unsigned char* w2=(const unsigned char*)g_W2p+(size_t)j*27*10240;
      uint32_t dep=depb; kc=0;
      #pragma unroll 1
      for(int i=0;i<27;i++){
        if(kc==0){ mbar_wait(dep,0,t0); dep+=8; fence_async_global(); }
        if(++kc==9) kc=0;
        mbar_wait(emptyb+8*s,ph,t0);
        uint32_t st=sb+s*STG, fb=fullb+8*s;
        mbar_expect_tx(fb,16384+10240);
        bulk_g2s(st+16384,w2,10240,fb);
        bulk_g2s(st,gp,16384,fb);
        gp+=16384; w2+=10240;
        if(++s==NSTG){s=0;ph^=1;}
      }
    } }
    else if(wid==9){
      #pragma unroll 1
      for(int sub=0;sub<3;sub++){
        bar_sync(5,160);
        if(elect_one()){
          bulk_s2g((unsigned char*)g_G+(size_t)(m*216+sub*72+j*9)*2048,sb+SM_GS,18432);
          bulk_commit(); bulk_wait0_read(); mbar_arrive_pred(gsb,1,1);
          bulk_wait0(); red_relaxed(g_gflag+m*96+sub*32); TS(26+sub);
        }
        __syncwarp();
      }
    }
    else if(wid==10){ if(elect_one()){
      flag_wait(g_cnt+64,(ep+1)*128,t0);
      #pragma unroll 1
      for(int sub=0;sub<3;sub++){ flag_wait(g_gflag+m*96+sub*32,(ep+1)*8,t0); mbar_arrive_pred(depb+8*sub,1,1); TS(23+sub); }
    } }
    else if(wg==3){
      if(lead) flag_wait(g_cnt,(ep+1)*512,t0);
      bar_sync(4,128);
      const unsigned tag=ep+1;
      float su[8], sq[8];
      #pragma unroll
      for(int e=0;e<8;e++){ su[e]=0; sq[e]=0; }
      const uint4* src=(const uint4*)(g_x1T+(size_t)(tl>>1)*L_+m*128+j*16+(tl&1)*8);
      #pragma unroll 1
      for(int h=0;h<2;h++){
        uint4 v[5];
        #pragma unroll
        for(int r=0;r<5;r++) v[r]=__ldcg(src+(size_t)(h*5+r)*64*L_/8);
        #pragma unroll
        for(int r=0;r<5;r++){
          uint32_t w[4]={v[r].x,v[r].y,v[r].z,v[r].w};
          #pragma unroll
          for(int e=0;e<4;e++){ float lo=bf_lo(w[e]), hi=bf_hi(w[e]); su[2*e]+=lo; sq[2*e]=fmaf(lo,lo,sq[2*e]); su[2*e+1]+=hi; sq[2*e+1]=fmaf(hi,hi,sq[2*e+1]); }
        }
      }
      float r8[8], r4[4], r2[2], r1;
      { bool up=lane&16;
        #pragma unroll
        for(int e=0;e<8;e++){ float snd=up?su[e]:sq[e], keep=up?sq[e]:su[e]; r8[e]=keep+__shfl_xor_sync(~0u,snd,16);} }
      { bool up=lane&8;
        #pragma unroll
        for(int e=0;e<4;e++){ float snd=up?r8[e]:r8[e+4], keep=up?r8[e+4]:r8[e]; r4[e]=keep+__shfl_xor_sync(~0u,snd,8);} }
      { bool up=lane&4;
        #pragma unroll
        for(int e=0;e<2;e++){ float snd=up?r4[e]:r4[e+2], keep=up?r4[e+2]:r4[e]; r2[e]=keep+__shfl_xor_sync(~0u,snd,4);} }
      { bool up=lane&2; float snd=up?r2[0]:r2[1], keep=up?r2[1]:r2[0]; r1=keep+__shfl_xor_sync(~0u,snd,2); }
      sts32f(sb+SM_GS+tl*4,r1);
      bar_sync(4,128);
      if(tl<16){
        float a=0,b=0;
        #pragma unroll
        for(int w=0;w<4;w++){ a+=lds32f(sb+SM_GS+(w*32+tl)*4); b+=lds32f(sb+SM_GS+(w*32+16+tl)*4); }
        float mu=a*(1.f/D_); float rs=rsqrtf(fmaxf(b*(1.f/D_)-mu*mu,0.f)+1e-5f);
        int tok=m*128+j*16+(tl&1)*8+(tl>>1);
        asm volatile("st.relaxed.gpu.global.v2.b64 [%0], {%1,%2};"::"l"(g_st2+tok),
          "l"(((unsigned long long)tag<<32)|__float_as_uint(rs)),"l"(((unsigned long long)tag<<32)|__float_as_uint(-rs*mu)):"memory");
      }
      #pragma unroll
      for(int i=0;i<2;i++){ int q=tl+128*i; if(q<216){ int f=(q/72)*576+j*72+q%72; float2 a=__ldcg(g_qs+f), b=__ldcg(g_qs+F_+f); sts128f(sb+SM_QS+q*16,make_float4(a.x,a.y,b.x,b.y)); } }
      { unsigned long long a,b;
        do{ asm volatile("ld.relaxed.gpu.global.v2.b64 {%0,%1}, [%2];":"=l"(a),"=l"(b):"l"(g_st2+m*128+tl):"memory");
        }while(((unsigned)(a>>32)!=tag || (unsigned)(b>>32)!=tag) && (int)(clk32()-t0)>=0);
        sts64f(sb+SM_ST+tl*8, __uint_as_float((unsigned)a), __uint_as_float((unsigned)b)); }
      bar_arrive(6,256); bar_arrive(7,256);
      TSP(29,lead);
    }
  } else {
    asm volatile("setmaxnreg.inc.sync.aligned.u32 208;");
    #pragma unroll 1
    for(int sub=wg; sub<3; sub+=2){
      float acc0[72], acc1[72];
      int i0=sub*10; int s=i0%NSTG, ph=(i0/NSTG)&1, ps=0;
      if(sub>0) bar_sync(7+sub,256);
      #pragma unroll 1
      for(int i=0;i<10;i++){
        mbar_wait(fullb+8*s,ph,t0);
        bar_arrive_pred(i==9? 8+sub : 11, 256, i==9 || (i==4 && sub==2));
        TSP(30+i0+i,lead);
        uint32_t st=sb+s*STG;
        uint64_t da=mkdesc(st,16,1024,1), db=mkdesc(st+16384,2304,128,0);
        wg_fence();
        #pragma unroll
        for(int kk=0;kk<4;kk++){
          wgmma_n144_tt(acc0, da+kk*128, db+kk*288, (i|kk)!=0);
          wgmma_n144_tt(acc1, da+512+kk*128, db+kk*288, (i|kk)!=0);
        }
        wg_commit();
        wg_wait<1>();
        mbar_arrive_pred(emptyb+8*ps,1,lead && i>0);
        ps=s; if(++s==NSTG){s=0;ph^=1;}
      }
      wg_wait<0>();
      reg_fence(acc0); reg_fence(acc1);
      mbar_arrive_pred(emptyb+8*ps,1,lead);
      TSP(88+sub,lead);
      if(sub<2) bar_sync(6+sub,256);
      if(sub>0) mbar_wait(gsb,(sub-1)&1,t0);
      float2 stt[4];
      #pragma unroll
      for(int r=0;r<4;r++) stt[r]=lds64f(sb+SM_ST+((r>>1)*64+warp*16+(r&1)*8+g)*8);
      const uint32_t qa=sb+SM_QS+(sub*72+2*t)*16;
      const uint32_t ga=sb+SM_GS+(((lane>>4)*64)+warp*16+((lane>>3)&1)*8+(lane&7))*16;
      float4 q0=lds128f(qa), q1=lds128f(qa+16);
      #pragma unroll
      for(int i=0;i<9;i++){
        float4 n0=q0, n1=q1;
        if(i<8){ n0=lds128f(qa+i*128+128); n1=lds128f(qa+i*128+144); }
        uint32_t o[4];
        #pragma unroll
        for(int r=0;r<4;r++){
          float res[2];
          #pragma unroll
          for(int e=0;e<2;e++){
            float4 q = e? q1:q0;
            float ag = (r>>1)? acc1[8*i+(r&1)*2+e] : acc0[8*i+(r&1)*2+e];
            float au = (r>>1)? acc1[8*i+4+(r&1)*2+e] : acc0[8*i+4+(r&1)*2+e];
            float gv = fmaf(stt[r].x, ag, fmaf(stt[r].y,q.x,q.y));
            float uv = fmaf(0.5f*stt[r].x, au, fmaf(stt[r].y,q.z,q.w));
            float z = gv*fmaf(gv*gv, 0.044715f*0.7978845608f, 0.7978845608f);
            float pr = gv*uv;
            res[e] = fmaf(pr, tanh_fast(z), pr);
          }
          o[r]=pack_bf16(res[0],res[1]);
        }
        stsm4(ga+i*2048,o[0],o[1],o[2],o[3]);
        q0=n0; q1=n1;
      }
      fence_async_smem();
      bar_arrive(5,160);
      TSP(91+sub,lead);
    }
    if(wg==1){
      float acc0[40], acc1[40]; uint32_t res[40]; float gbv[20];
      #pragma unroll
      for(int i=0;i<20;i++) gbv[i]=__uint_as_float(ld_relaxed(g_mod+5*D_+j*80+8*(i>>1)+2*t+(i&1)));
      { const uint32_t tag16=(cnt0>>9)%65535u+1;
        #pragma unroll
        for(int i=0;i<20;i++){ uint32_t v=__float_as_uint(gbv[i]); if((v&0xffffu)!=tag16) v=mod_wait(g_mod+5*D_+j*80+8*(i>>1)+2*t+(i&1),tag16,t0); gbv[i]=bf_hi(v); } }
      int s=30%NSTG, ph=(30/NSTG)&1, ps=0;
      bar_sync(11,256);
      { mbar_wait(fullb+8*s,ph,t0);
        uint32_t a=sb+s*STG+(lane>>4)*10240+(lane&7)*128+(((2*warp+((lane>>3)&1))^(lane&7))<<4);
        #pragma unroll
        for(int i=0;i<10;i++) ldsm4t(a+i*1024,res[4*i],res[4*i+1],res[4*i+2],res[4*i+3]);
        bar_sync(2,128);
        mbar_arrive_pred(emptyb+8*s,1,lead);
        if(++s==NSTG){s=0;ph^=1;} }
      bar_sync(10,256);
      #pragma unroll 1
      for(int i=0;i<27;i++){
        mbar_wait(fullb+8*s,ph,t0);
        TSP(61+i,lead);
        uint32_t st=sb+s*STG;
        uint64_t da=mkdesc(st,2048,128,0), db=mkdesc(st+16384,2048,256,3);
        wg_fence();
        #pragma unroll
        for(int kk=0;kk<4;kk++){
          wgmma_n80_nt(acc0, da+kk*256, db+kk*32, (i|kk)!=0);
          wgmma_n80_nt(acc1, da+64+kk*256, db+kk*32, (i|kk)!=0);
        }
        wg_commit();
        wg_wait<1>();
        mbar_arrive_pred(emptyb+8*ps,1,lead && i>0);
        ps=s; if(++s==NSTG){s=0;ph^=1;}
      }
      wg_wait<0>();
      reg_fence(acc0); reg_fence(acc1);
      TSP(94,lead);
      const uint32_t ob=sb+s*STG;
      const uint32_t oa=ob+(((lane>>4)*64)+warp*16+((lane>>3)&1)*8+(lane&7))*160;
      #pragma unroll
      for(int i=0;i<10;i++){
        uint32_t o[4];
        #pragma unroll
        for(int r=0;r<4;r++){
          float a0=(r>>1)? acc1[4*i+(r&1)*2] : acc0[4*i+(r&1)*2];
          float a1=(r>>1)? acc1[4*i+(r&1)*2+1] : acc0[4*i+(r&1)*2+1];
          o[r]=pack_bf16(fmaf(gbv[2*i],a0,bf_lo(res[4*i+r])), fmaf(gbv[2*i+1],a1,bf_hi(res[4*i+r])));
        }
        stsm4(oa+i*16,o[0],o[1],o[2],o[3]);
      }
      fence_async_smem();
      __syncwarp();
      if(elect_one()){
        tma_st2(&p.out, j*80, m*128+warp*16, ob+warp*2560);
        tma_st2(&p.out, j*80, m*128+64+warp*16, ob+(4+warp)*2560);
        bulk_commit();
        bulk_wait0_read();
      }
      __syncwarp();
      TSP(95,lead);
    }
  }
}

typedef CUresult (*EncFn)(CUtensorMap*, CUtensorMapDataType, cuuint32_t, void*, const cuuint64_t*, const cuuint64_t*, const cuuint32_t*, const cuuint32_t*, CUtensorMapInterleave, CUtensorMapSwizzle, CUtensorMapL2promotion, CUtensorMapFloatOOBfill);
static void mk2(EncFn enc, CUtensorMap* m, const void* p, cuuint64_t d0, cuuint64_t d1, cuuint64_t s1, cuuint32_t b0, cuuint32_t b1, CUtensorMapSwizzle sw){
  cuuint64_t gd[2]={d0,d1}, gs[1]={s1}; cuuint32_t bx[2]={b0,b1}, es[2]={1,1};
  CUresult r=enc(m,CU_TENSOR_MAP_DATA_TYPE_BFLOAT16,2,(void*)p,gd,gs,bx,es,CU_TENSOR_MAP_INTERLEAVE_NONE,sw,CU_TENSOR_MAP_L2_PROMOTION_NONE,CU_TENSOR_MAP_FLOAT_OOB_FILL_NONE);
  (void)r;
}
extern "C" void kernel_launch(void* const* d_in, const int* in_sizes, int n_in, void* d_out, int out_size){
  Params p;
  p.x=(const bf16*)d_in[0]; p.lA=(const bf16*)d_in[1]; p.Ai=(const bf16*)d_in[2]; p.Cr=(const bf16*)d_in[3]; p.Ci=(const bf16*)d_in[4];
  p.ldt=(const bf16*)d_in[5]; p.Dsk=(const bf16*)d_in[6]; p.wgp=(const bf16*)d_in[8]; p.wup=(const bf16*)d_in[9]; p.wdp=(const bf16*)d_in[10]; p.c=(const bf16*)d_in[11];
  const bf16* wm=(const bf16*)d_in[12]; p.zero=0;
  EncFn enc=nullptr; cudaDriverEntryPointQueryResult qr;
  cudaGetDriverEntryPoint("cuTensorMapEncodeTiled",(void**)&enc,cudaEnableDefault,&qr);
  void *px1,*pin,*pwp; cudaGetSymbolAddress(&px1,g_x1T); cudaGetSymbolAddress(&pin,g_inbox); cudaGetSymbolAddress(&pwp,g_Wp);
  mk2(enc,&p.x1a,px1,L_,D_,L_*2,64,64,CU_TENSOR_MAP_SWIZZLE_128B);
  mk2(enc,&p.x1r,px1,L_,D_,L_*2,64,80,CU_TENSOR_MAP_SWIZZLE_128B);
  mk2(enc,&p.out,d_out,D_,L_,D_*2,80,16,CU_TENSOR_MAP_SWIZZLE_NONE);
  mk2(enc,&p.xts,px1,L_,D_,L_*2,16,160,CU_TENSOR_MAP_SWIZZLE_32B);
  mk2(enc,&p.xns,pin,128*80,128,128*160,80,128,CU_TENSOR_MAP_SWIZZLE_NONE);
  mk2(enc,&p.x1red,px1,64,D_*32,128,64,32,CU_TENSOR_MAP_SWIZZLE_128B);
  mk2(enc,&p.wm,wm,6*D_,D_,6*D_*2,32,160,CU_TENSOR_MAP_SWIZZLE_64B);
  mk2(enc,&p.wg,p.wgp,F_,D_,F_*2,32,160,CU_TENSOR_MAP_SWIZZLE_64B);
  mk2(enc,&p.wu,p.wup,F_,D_,F_*2,32,160,CU_TENSOR_MAP_SWIZZLE_64B);
  mk2(enc,&p.wps,pwp,1152,24*80,2304,64,80,CU_TENSOR_MAP_SWIZZLE_NONE);
  { cuuint64_t gd[3]={16,F_,40}, gs[2]={D_*2,32}; cuuint32_t bx[3]={16,64,5}, es[3]={1,1,1};
    CUresult r=enc(&p.w2l,CU_TENSOR_MAP_DATA_TYPE_BFLOAT16,3,(void*)p.wdp,gd,gs,bx,es,CU_TENSOR_MAP_INTERLEAVE_NONE,CU_TENSOR_MAP_SWIZZLE_32B,CU_TENSOR_MAP_L2_PROMOTION_NONE,CU_TENSOR_MAP_FLOAT_OOB_FILL_NONE);
    (void)r; }
  cudaFuncSetAttribute(fused_kernel,cudaFuncAttributeMaxDynamicSharedMemorySize,SM_ALLOC);
  fused_kernel<<<128,512,SM_ALLOC>>>(p);
}
```

```cpp
#include <cuda_runtime.h>
#include <cuda_bf16.h>
#include <cuda_fp16.h>
#include <cuda.h>
#include <stdint.h>

typedef __nv_bfloat16 bf16;
constexpr int L_ = 2048, D_ = 640, N_ = 128, F_ = 1728;

__device__ __forceinline__ uint32_t smem_u32(const void* p){ return (uint32_t)__cvta_generic_to_shared(p); }
__device__ __forceinline__ uint32_t opaque(uint32_t x){ uint32_t y; asm volatile("mov.u32 %0, %1;":"=r"(y):"r"(x)); return y; }
__device__ __forceinline__ uint32_t clk32(){ uint32_t c; asm volatile("mov.u32 %0, %%clock;":"=r"(c)); return c; }
__device__ __forceinline__ bool elect_one(){ uint32_t p; asm volatile("{\n.reg .pred P;\nelect.sync _|P, 0xffffffff;\nselp.u32 %0,1,0,P;\n}":"=r"(p)); return p; }
__device__ __forceinline__ void mbar_init(uint32_t bar, uint32_t cnt){ asm volatile("mbarrier.init.shared::cta.b64 [%0], %1;"::"r"(bar),"r"(cnt):"memory"); }
__device__ __forceinline__ void mbar_expect_tx(uint32_t bar, uint32_t bytes){ asm volatile("mbarrier.arrive.expect_tx.shared::cta.b64 _, [%0], %1;"::"r"(bar),"r"(bytes):"memory"); }
__device__ __forceinline__ void mbar_arrive_pred(uint32_t bar, uint32_t cnt, int pred){
  asm volatile("{\n.reg .pred p;\nsetp.ne.b32 p, %2, 0;\n@p mbarrier.arrive.shared::cta.b64 _, [%0], %1;\n}"::"r"(bar),"r"(cnt),"r"(pred):"memory"); }
__device__ __forceinline__ void mbar_wait(uint32_t bar, uint32_t parity, uint32_t){
  asm volatile("{\n.reg .pred p;\n.reg .b32 c;\nmbarrier.try_wait.parity.shared::cta.b64 p, [%0], %1;\n@p bra LD;\nmov.u32 c, 0;\n"
               "LW:\nmbarrier.try_wait.parity.shared::cta.b64 p, [%0], %1;\n@p bra LD;\nadd.u32 c, c, 1;\nsetp.lt.u32 p, c, 262144;\n@p bra LW;\nLD:\n}"::"r"(bar),"r"(parity):"memory"); }
__device__ __forceinline__ void flag_wait(const unsigned* f, unsigned target, uint32_t t0){
  asm volatile("{\n.reg .pred p;\n.reg .b32 c;\nLW:\nld.acquire.gpu.global.u32 c, [%0];\nsub.u32 c, c, %1;\nsetp.ge.s32 p, c, 0;\n@p bra LD;\n"
               "mov.u32 c, %%clock;\nsub.u32 c, c, %2;\nsetp.lt.s32 p, c, 0;\n@p bra LD;\nbra LW;\nLD:\n}"::"l"(f),"r"(target),"r"(t0):"memory"); }
__device__ __forceinline__ void red_release(unsigned* f, unsigned v){ asm volatile("red.release.gpu.global.add.u32 [%0], %1;"::"l"(f),"r"(v):"memory"); }
__device__ __forceinline__ unsigned ld_relaxed(const unsigned* f){ unsigned v; asm volatile("ld.relaxed.gpu.global.u32 %0, [%1];":"=r"(v):"l"(f):"memory"); return v; }
__device__ __forceinline__ void fence_async_smem(){ asm volatile("fence.proxy.async.shared::cta;":::"memory"); }
__device__ __forceinline__ void fence_async_all(){ asm volatile("fence.proxy.async;":::"memory"); }
__device__ __forceinline__ void bar_sync(int id, int n){ asm volatile("bar.sync %0, %1;"::"r"(id),"r"(n):"memory"); }
__device__ __forceinline__ void bar_arrive(int id, int n){ asm volatile("bar.arrive %0, %1;"::"r"(id),"r"(n):"memory"); }
__device__ __forceinline__ void bulk_g2s(uint32_t dst, const void* src, uint32_t bytes, uint32_t bar){
  asm volatile("cp.async.bulk.shared::cluster.global.mbarrier::complete_tx::bytes [%0], [%1], %2, [%3];"::"r"(dst),"l"(src),"r"(bytes),"r"(bar):"memory"); }
__device__ __forceinline__ void tma_ld2(uint32_t dst, const CUtensorMap* m, int c0, int c1, uint32_t bar){
  asm volatile("cp.async.bulk.tensor.2d.shared::cluster.global.mbarrier::complete_tx::bytes [%0], [%1, {%3, %4}], [%2];"::"r"(dst),"l"(m),"r"(bar),"r"(c0),"r"(c1):"memory"); }
__device__ __forceinline__ void tma_ld3(uint32_t dst, const CUtensorMap* m, int c0, int c1, int c2, uint32_t bar){
  asm volatile("cp.async.bulk.tensor.3d.shared::cluster.global.mbarrier::complete_tx::bytes [%0], [%1, {%3, %4, %5}], [%2];"::"r"(dst),"l"(m),"r"(bar),"r"(c0),"r"(c1),"r"(c2):"memory"); }
__device__ __forceinline__ void tma_st2(const CUtensorMap* m, int c0, int c1, uint32_t src){
  asm volatile("cp.async.bulk.tensor.2d.global.shared::cta.bulk_group [%0, {%2, %3}], [%1];"::"l"(m),"r"(src),"r"(c0),"r"(c1):"memory"); }
__device__ __forceinline__ void bulk_commit(){ asm volatile("cp.async.bulk.commit_group;":::"memory"); }
__device__ __forceinline__ void bulk_wait0(){ asm volatile("cp.async.bulk.wait_group 0;":::"memory"); }
__device__ __forceinline__ void bulk_wait0_read(){ asm volatile("cp.async.bulk.wait_group.read 0;":::"memory"); }
__device__ __forceinline__ void prefetch_tmap(const CUtensorMap* m){ asm volatile("prefetch.tensormap [%0];"::"l"(m):"memory"); }
__device__ __forceinline__ void wg_fence(){ asm volatile("wgmma.fence.sync.aligned;":::"memory"); }
__device__ __forceinline__ void wg_commit(){ asm volatile("wgmma.commit_group.sync.aligned;":::"memory"); }
template<int N> __device__ __forceinline__ void wg_wait(){ asm volatile("wgmma.wait_group.sync.aligned %0;"::"n"(N):"memory"); }
template<int N> __device__ __forceinline__ void reg_fence(float (&d)[N]){
  #pragma unroll
  for(int i=0;i<N;i++) asm volatile("":"+f"(d[i])::"memory"); }
__device__ __forceinline__ uint64_t mkdesc(uint32_t addr, uint32_t lbo, uint32_t sbo, uint32_t swz){
  return (uint64_t)((addr&0x3FFFF)>>4) | ((uint64_t)(lbo>>4)<<16) | ((uint64_t)(sbo>>4)<<32) | ((uint64_t)swz<<62); }
__device__ __forceinline__ void stsm4(uint32_t a, uint32_t r0, uint32_t r1, uint32_t r2, uint32_t r3){
  asm volatile("stmatrix.sync.aligned.m8n8.x4.shared.b16 [%0], {%1,%2,%3,%4};"::"r"(a),"r"(r0),"r"(r1),"r"(r2),"r"(r3):"memory"); }
__device__ __forceinline__ void stsm4t(uint32_t a, uint32_t r0, uint32_t r1, uint32_t r2, uint32_t r3){
  asm volatile("stmatrix.sync.aligned.m8n8.x4.trans.shared.b16 [%0], {%1,%2,%3,%4};"::"r"(a),"r"(r0),"r"(r1),"r"(r2),"r"(r3):"memory"); }
__device__ __forceinline__ void ldsm4t(uint32_t a, uint32_t& r0, uint32_t& r1, uint32_t& r2, uint32_t& r3){
  asm volatile("ldmatrix.sync.aligned.m8n8.x4.trans.shared.b16 {%0,%1,%2,%3}, [%4];":"=r"(r0),"=r"(r1),"=r"(r2),"=r"(r3):"r"(a):"memory"); }
__device__ __forceinline__ uint4 lds128(uint32_t a){ uint4 v; asm volatile("ld.shared.v4.u32 {%0,%1,%2,%3}, [%4];":"=r"(v.x),"=r"(v.y),"=r"(v.z),"=r"(v.w):"r"(a):"memory"); return v; }
__device__ __forceinline__ float4 lds128f(uint32_t a){ float4 v; asm volatile("ld.shared.v4.f32 {%0,%1,%2,%3}, [%4];":"=f"(v.x),"=f"(v.y),"=f"(v.z),"=f"(v.w):"r"(a):"memory"); return v; }
__device__ __forceinline__ float2 lds64f(uint32_t a){ float2 v; asm volatile("ld.shared.v2.f32 {%0,%1}, [%2];":"=f"(v.x),"=f"(v.y):"r"(a):"memory"); return v; }
__device__ __forceinline__ void sts64f(uint32_t a, float x, float y){ asm volatile("st.shared.v2.f32 [%0], {%1,%2};"::"r"(a),"f"(x),"f"(y):"memory"); }
__device__ __forceinline__ void sts128f(uint32_t a, float4 v){ asm volatile("st.shared.v4.f32 [%0], {%1,%2,%3,%4};"::"r"(a),"f"(v.x),"f"(v.y),"f"(v.z),"f"(v.w):"memory"); }
__device__ __forceinline__ uint32_t pack_bf16(float lo, float hi){ uint32_t r; asm("cvt.rn.bf16x2.f32 %0, %1, %2;":"=r"(r):"f"(hi),"f"(lo)); return r; }
__device__ __forceinline__ float bf_lo(uint32_t v){ return __uint_as_float(v<<16); }
__device__ __forceinline__ float bf_hi(uint32_t v){ return __uint_as_float(v&0xffff0000u); }
__device__ __forceinline__ float tanh_fast(float x){ float y; asm("tanh.approx.f32 %0, %1;":"=f"(y):"f"(x)); return y; }
__device__ __forceinline__ float bfr(float x){ return __uint_as_float(pack_bf16(0.f,x)); }

__device__ __forceinline__ void wgmma_n144_tt(float (&d)[72], uint64_t da, uint64_t db, int sc){
  asm volatile("{\n.reg .pred p;\nsetp.ne.b32 p, %74, 0;\nwgmma.mma_async.sync.aligned.m64n144k16.f32.bf16.bf16 {%0,%1,%2,%3,%4,%5,%6,%7,%8,%9,%10,%11,%12,%13,%14,%15,%16,%17,%18,%19,%20,%21,%22,%23,%24,%25,%26,%27,%28,%29,%30,%31,%32,%33,%34,%35,%36,%37,%38,%39,%40,%41,%42,%43,%44,%45,%46,%47,%48,%49,%50,%51,%52,%53,%54,%55,%56,%57,%58,%59,%60,%61,%62,%63,%64,%65,%66,%67,%68,%69,%70,%71}, %72, %73, p, 1, 1, 1, 1;\n}\n"
   : "+f"(d[0]),"+f"(d[1]),"+f"(d[2]),"+f"(d[3]),"+f"(d[4]),"+f"(d[5]),"+f"(d[6]),"+f"(d[7]),"+f"(d[8]),"+f"(d[9]),"+f"(d[10]),"+f"(d[11]),"+f"(d[12]),"+f"(d[13]),"+f"(d[14]),"+f"(d[15]),"+f"(d[16]),"+f"(d[17]),"+f"(d[18]),"+f"(d[19]),"+f"(d[20]),"+f"(d[21]),"+f"(d[22]),"+f"(d[23]),"+f"(d[24]),"+f"(d[25]),"+f"(d[26]),"+f"(d[27]),"+f"(d[28]),"+f"(d[29]),"+f"(d[30]),"+f"(d[31]),"+f"(d[32]),"+f"(d[33]),"+f"(d[34]),"+f"(d[35]),"+f"(d[36]),"+f"(d[37]),"+f"(d[38]),"+f"(d[39]),"+f"(d[40]),"+f"(d[41]),"+f"(d[42]),"+f"(d[43]),"+f"(d[44]),"+f"(d[45]),"+f"(d[46]),"+f"(d[47]),"+f"(d[48]),"+f"(d[49]),"+f"(d[50]),"+f"(d[51]),"+f"(d[52]),"+f"(d[53]),"+f"(d[54]),"+f"(d[55]),"+f"(d[56]),"+f"(d[57]),"+f"(d[58]),"+f"(d[59]),"+f"(d[60]),"+f"(d[61]),"+f"(d[62]),"+f"(d[63]),"+f"(d[64]),"+f"(d[65]),"+f"(d[66]),"+f"(d[67]),"+f"(d[68]),"+f"(d[69]),"+f"(d[70]),"+f"(d[71])
   : "l"(da), "l"(db), "r"(sc));
}

__device__ __forceinline__ void wgmma_n80_nt(float (&d)[40], uint64_t da, uint64_t db, int sc){
  asm volatile("{\n.reg .pred p;\nsetp.ne.b32 p, %42, 0;\nwgmma.mma_async.sync.aligned.m64n80k16.f32.bf16.bf16 {%0,%1,%2,%3,%4,%5,%6,%7,%8,%9,%10,%11,%12,%13,%14,%15,%16,%17,%18,%19,%20,%21,%22,%23,%24,%25,%26,%27,%28,%29,%30,%31,%32,%33,%34,%35,%36,%37,%38,%39}, %40, %41, p, 1, 1, 0, 1;\n}\n"
   : "+f"(d[0]),"+f"(d[1]),"+f"(d[2]),"+f"(d[3]),"+f"(d[4]),"+f"(d[5]),"+f"(d[6]),"+f"(d[7]),"+f"(d[8]),"+f"(d[9]),"+f"(d[10]),"+f"(d[11]),"+f"(d[12]),"+f"(d[13]),"+f"(d[14]),"+f"(d[15]),"+f"(d[16]),"+f"(d[17]),"+f"(d[18]),"+f"(d[19]),"+f"(d[20]),"+f"(d[21]),"+f"(d[22]),"+f"(d[23]),"+f"(d[24]),"+f"(d[25]),"+f"(d[26]),"+f"(d[27]),"+f"(d[28]),"+f"(d[29]),"+f"(d[30]),"+f"(d[31]),"+f"(d[32]),"+f"(d[33]),"+f"(d[34]),"+f"(d[35]),"+f"(d[36]),"+f"(d[37]),"+f"(d[38]),"+f"(d[39])
   : "l"(da), "l"(db), "r"(sc));
}

__device__ __forceinline__ void wgmma_n64_rs(float (&d)[32], uint32_t a0, uint32_t a1, uint32_t a2, uint32_t a3, uint64_t db, int sc){
  asm volatile("{\n.reg .pred p;\nsetp.ne.b32 p, %37, 0;\nwgmma.mma_async.sync.aligned.m64n64k16.f32.bf16.bf16 {%0,%1,%2,%3,%4,%5,%6,%7,%8,%9,%10,%11,%12,%13,%14,%15,%16,%17,%18,%19,%20,%21,%22,%23,%24,%25,%26,%27,%28,%29,%30,%31}, {%32,%33,%34,%35}, %36, p, 1, 1, 0;\n}\n"
   : "+f"(d[0]),"+f"(d[1]),"+f"(d[2]),"+f"(d[3]),"+f"(d[4]),"+f"(d[5]),"+f"(d[6]),"+f"(d[7]),"+f"(d[8]),"+f"(d[9]),"+f"(d[10]),"+f"(d[11]),"+f"(d[12]),"+f"(d[13]),"+f"(d[14]),"+f"(d[15]),"+f"(d[16]),"+f"(d[17]),"+f"(d[18]),"+f"(d[19]),"+f"(d[20]),"+f"(d[21]),"+f"(d[22]),"+f"(d[23]),"+f"(d[24]),"+f"(d[25]),"+f"(d[26]),"+f"(d[27]),"+f"(d[28]),"+f"(d[29]),"+f"(d[30]),"+f"(d[31])
   : "r"(a0),"r"(a1),"r"(a2),"r"(a3), "l"(db), "r"(sc));
}

__device__ __forceinline__ void wgmma_n48_rs(float (&d)[32], uint32_t a0, uint32_t a1, uint32_t a2, uint32_t a3, uint64_t db, int sc){
  asm volatile("{\n.reg .pred p;\nsetp.ne.b32 p, %29, 0;\nwgmma.mma_async.sync.aligned.m64n48k16.f32.bf16.bf16 {%0,%1,%2,%3,%4,%5,%6,%7,%8,%9,%10,%11,%12,%13,%14,%15,%16,%17,%18,%19,%20,%21,%22,%23}, {%24,%25,%26,%27}, %28, p, 1, 1, 0;\n}\n"
   : "+f"(d[0]),"+f"(d[1]),"+f"(d[2]),"+f"(d[3]),"+f"(d[4]),"+f"(d[5]),"+f"(d[6]),"+f"(d[7]),"+f"(d[8]),"+f"(d[9]),"+f"(d[10]),"+f"(d[11]),"+f"(d[12]),"+f"(d[13]),"+f"(d[14]),"+f"(d[15]),"+f"(d[16]),"+f"(d[17]),"+f"(d[18]),"+f"(d[19]),"+f"(d[20]),"+f"(d[21]),"+f"(d[22]),"+f"(d[23])
   : "r"(a0),"r"(a1),"r"(a2),"r"(a3), "l"(db), "r"(sc));
}

__device__ __forceinline__ void wgmma_n32_rs(float (&d)[32], uint32_t a0, uint32_t a1, uint32_t a2, uint32_t a3, uint64_t db, int sc){
  asm volatile("{\n.reg .pred p;\nsetp.ne.b32 p, %21, 0;\nwgmma.mma_async.sync.aligned.m64n32k16.f32.bf16.bf16 {%0,%1,%2,%3,%4,%5,%6,%7,%8,%9,%10,%11,%12,%13,%14,%15}, {%16,%17,%18,%19}, %20, p, 1, 1, 0;\n}\n"
   : "+f"(d[0]),"+f"(d[1]),"+f"(d[2]),"+f"(d[3]),"+f"(d[4]),"+f"(d[5]),"+f"(d[6]),"+f"(d[7]),"+f"(d[8]),"+f"(d[9]),"+f"(d[10]),"+f"(d[11]),"+f"(d[12]),"+f"(d[13]),"+f"(d[14]),"+f"(d[15])
   : "r"(a0),"r"(a1),"r"(a2),"r"(a3), "l"(db), "r"(sc));
}

__device__ __forceinline__ void wgmma_n32_tn(float (&d)[32], uint64_t da, uint64_t db, int sc){
  asm volatile("{\n.reg .pred p;\nsetp.ne.b32 p, %18, 0;\nwgmma.mma_async.sync.aligned.m64n32k16.f32.bf16.bf16 {%0,%1,%2,%3,%4,%5,%6,%7,%8,%9,%10,%11,%12,%13,%14,%15}, %16, %17, p, 1, 1, 1, 0;\n}\n"
   : "+f"(d[0]),"+f"(d[1]),"+f"(d[2]),"+f"(d[3]),"+f"(d[4]),"+f"(d[5]),"+f"(d[6]),"+f"(d[7]),"+f"(d[8]),"+f"(d[9]),"+f"(d[10]),"+f"(d[11]),"+f"(d[12]),"+f"(d[13]),"+f"(d[14]),"+f"(d[15])
   : "l"(da), "l"(db), "r"(sc));
}

__device__ __forceinline__ void wgmma_n16_f16(float (&d)[8], uint64_t da, uint64_t db, int sc){
  asm volatile("{\n.reg .pred p;\nsetp.ne.b32 p, %10, 0;\nwgmma.mma_async.sync.aligned.m64n16k16.f32.f16.f16 {%0,%1,%2,%3,%4,%5,%6,%7}, %8, %9, p, 1, 1, 1, 1;\n}\n"
   : "+f"(d[0]),"+f"(d[1]),"+f"(d[2]),"+f"(d[3]),"+f"(d[4]),"+f"(d[5]),"+f"(d[6]),"+f"(d[7])
   : "l"(da), "l"(db), "r"(sc));
}

__device__ __forceinline__ void ldsm4(uint32_t a, uint32_t& r0, uint32_t& r1, uint32_t& r2, uint32_t& r3){
  asm volatile("ldmatrix.sync.aligned.m8n8.x4.shared.b16 {%0,%1,%2,%3}, [%4];":"=r"(r0),"=r"(r1),"=r"(r2),"=r"(r3):"r"(a):"memory"); }
__device__ __forceinline__ void mma_bf16(float (&d)[4], uint32_t a0,uint32_t a1,uint32_t a2,uint32_t a3,uint32_t b0,uint32_t b1){
  asm("mma.sync.aligned.m16n8k16.row.col.f32.bf16.bf16.f32 {%0,%1,%2,%3},{%4,%5,%6,%7},{%8,%9},{%0,%1,%2,%3};"
   :"+f"(d[0]),"+f"(d[1]),"+f"(d[2]),"+f"(d[3]):"r"(a0),"r"(a1),"r"(a2),"r"(a3),"r"(b0),"r"(b1)); }
__device__ __forceinline__ void mma_f16(float (&d)[4], uint32_t a0,uint32_t a1,uint32_t a2,uint32_t a3,uint32_t b0,uint32_t b1){
  asm("mma.sync.aligned.m16n8k16.row.col.f32.f16.f16.f32 {%0,%1,%2,%3},{%4,%5,%6,%7},{%8,%9},{%0,%1,%2,%3};"
   :"+f"(d[0]),"+f"(d[1]),"+f"(d[2]),"+f"(d[3]):"r"(a0),"r"(a1),"r"(a2),"r"(a3),"r"(b0),"r"(b1)); }
__device__ __forceinline__ uint32_t lds32(uint32_t a){ uint32_t v; asm volatile("ld.shared.u32 %0, [%1];":"=r"(v):"r"(a):"memory"); return v; }
__device__ __forceinline__ float lds32f(uint32_t a){ float v; asm volatile("ld.shared.f32 %0, [%1];":"=f"(v):"r"(a):"memory"); return v; }
__device__ __forceinline__ uint32_t lds16(uint32_t a){ uint32_t v; asm volatile("ld.shared.u16 %0, [%1];":"=r"(v):"r"(a):"memory"); return v; }
__device__ __forceinline__ uint2 lds64(uint32_t a){ uint2 v; asm volatile("ld.shared.v2.u32 {%0,%1}, [%2];":"=r"(v.x),"=r"(v.y):"r"(a):"memory"); return v; }
__device__ __forceinline__ void sts16(uint32_t a, uint32_t v){ asm volatile("st.shared.u16 [%0], %1;"::"r"(a),"h"((unsigned short)v):"memory"); }
__device__ __forceinline__ void sts32(uint32_t a, uint32_t v){ asm volatile("st.shared.u32 [%0], %1;"::"r"(a),"r"(v):"memory"); }
__device__ __forceinline__ void sts32f(uint32_t a, float v){ asm volatile("st.shared.f32 [%0], %1;"::"r"(a),"f"(v):"memory"); }
__device__ __forceinline__ void sts64(uint32_t a, uint32_t x, uint32_t y){ asm volatile("st.shared.v2.u32 [%0], {%1,%2};"::"r"(a),"r"(x),"r"(y):"memory"); }
__device__ __forceinline__ void sts128(uint32_t a, uint32_t x, uint32_t y, uint32_t z, uint32_t w){ asm volatile("st.shared.v4.u32 [%0], {%1,%2,%3,%4};"::"r"(a),"r"(x),"r"(y),"r"(z),"r"(w):"memory"); }
__device__ __forceinline__ uint32_t prmt(uint32_t a, uint32_t b, uint32_t s){ uint32_t r; asm("prmt.b32 %0,%1,%2,%3;":"=r"(r):"r"(a),"r"(b),"r"(s)); return r; }
__device__ __forceinline__ uint32_t pack_h2(float lo, float hi){ uint32_t r; asm("cvt.rn.f16x2.f32 %0, %1, %2;":"=r"(r):"f"(hi),"f"(lo)); return r; }
__device__ __forceinline__ uint32_t bf2_mul(uint32_t a, uint32_t b){ uint32_t r; asm("mul.rn.bf16x2 %0,%1,%2;":"=r"(r):"r"(a),"r"(b)); return r; }
__device__ __forceinline__ uint32_t bf2_add(uint32_t a, uint32_t b){ uint32_t r; asm("add.rn.bf16x2 %0,%1,%2;":"=r"(r):"r"(a),"r"(b)); return r; }
__device__ __forceinline__ uint32_t bf2_fma(uint32_t a, uint32_t b, uint32_t c){ uint32_t r; asm("fma.rn.bf16x2 %0,%1,%2,%3;":"=r"(r):"r"(a),"r"(b),"r"(c)); return r; }
__device__ __forceinline__ uint32_t bf_bits(float x){ return pack_bf16(x,0.f)&0xffffu; }
__device__ __forceinline__ void red_relaxed(unsigned* f){ asm volatile("red.relaxed.gpu.global.add.u32 [%0], 1;"::"l"(f):"memory"); }
__device__ __forceinline__ void fence_async_global(){ asm volatile("fence.proxy.async.global;":::"memory"); }
__device__ __forceinline__ void bulk_s2g(void* dst, uint32_t src, uint32_t bytes){ asm volatile("cp.async.bulk.global.shared::cta.bulk_group [%0], [%1], %2;"::"l"(dst),"r"(src),"r"(bytes):"memory"); }
__device__ __forceinline__ void tma_red2(const CUtensorMap* m, int c0, int c1, uint32_t src){
  asm volatile("cp.reduce.async.bulk.tensor.2d.global.shared::cta.add.bulk_group [%0, {%2, %3}], [%1];"::"l"(m),"r"(src),"r"(c0),"r"(c1):"memory"); }
__device__ __forceinline__ void l2_prefetch(const void* p, uint32_t bytes){ asm volatile("cp.async.bulk.prefetch.L2.global [%0], %1;"::"l"(p),"r"(bytes):"memory"); }
__device__ __forceinline__ void bar_arrive_pred(int id, int n, int pred){ asm volatile("{\n.reg .pred p;\nsetp.ne.b32 p, %2, 0;\n@p bar.arrive %0, %1;\n}"::"r"(id),"r"(n),"r"(pred):"memory"); }
__device__ __forceinline__ float sqrt_fast(float x){ float y; asm("sqrt.approx.f32 %0, %1;":"=f"(y):"f"(x)); return y; }
struct cf { float x, y; };
__device__ __forceinline__ cf csq(cf a){ cf r; r.x=fmaf(a.x,a.x,-a.y*a.y); r.y=(a.x+a.x)*a.y; return r; }
__device__ __forceinline__ cf cmul(cf a, cf b){ cf r; r.x=fmaf(a.x,b.x,-a.y*b.y); r.y=fmaf(a.x,b.y,a.y*b.x); return r; }
__device__ __forceinline__ cf cexp_dir(float l2, float turns){
  float r=(turns-__fadd_rn(__fadd_rn(turns,12582912.f),-12582912.f))*6.283185307179586f, m; asm("ex2.approx.ftz.f32 %0, %1;":"=f"(m):"f"(l2));
  cf e; e.x=m*__cosf(r); e.y=m*__sinf(r); return e; }
__device__ __forceinline__ void hmulc(uint32_t re, uint32_t im, uint32_t m, uint32_t& ore, uint32_t& oim){
  __half2 R=*(__half2*)&re, I=*(__half2*)&im, M=*(__half2*)&m; __half2 c=__low2half2(M), d=__high2half2(M);
  __half2 a=__hfma2(c,R,__hneg2(__hmul2(d,I))), b=__hfma2(c,I,__hmul2(d,R)); ore=*(uint32_t*)&a; oim=*(uint32_t*)&b; }

struct Scratch {
  bf16 inbox[128*128*80];
  bf16 x1T[D_*L_];
  bf16 Wp[D_*2*F_];
  bf16 W2p[F_*D_];
  bf16 G[L_*F_];
  float2 qs[2*F_];
  ulonglong2 st2[8*L_];
  unsigned mod[6*D_];
  unsigned cnt[4*32];
  unsigned gflag[16*32];
};
__device__ __align__(1024) Scratch g_scr;

#define CBM 12
#define CB0 (CBM==12?9:13)
#define HINT_EARLY 0
#define PROMO CU_TENSOR_MAP_L2_PROMOTION_NONE
#define EPI 5
#define REL1 3
#define REL2 3
#define RESAT 26
#define POLLNS 100
#define EPI2 0
#define STP 2
#define PDEPTH 1
#define STNS 100
#define XW 2
#define XF 1
#define STAG 2
#define W1PF 0
#define GATE 1
#define B23 0
#define V4 0
#define W2A 6
#define W2N 3
#define W2PF 1
#define X_DELAY 200
#define WM_EARLY 1800
#define WM_LATE 3000
constexpr int NSTG = 6, STG = 34816;
constexpr int SM_GS = NSTG*STG, SM_QS = SM_GS+18432, SM_ST = SM_QS+3456, SM_BAR = SM_ST+1024, SM_TOTAL = SM_BAR+384;
constexpr int NST2 = 7, STG2 = 26624, SM_RES = NST2*STG2;
constexpr int SM_KG = 0, KG_WG = 28672;
constexpr int SM_TB = 3*KG_WG;
constexpr int SM_XS = SM_TB+5*8192, SM_XR = SM_XS+20480, SM_WM = SM_XR+21504, SM_MI = SM_WM+40960, SM_FT = SM_MI+5376, FT_WG = 1664, SM_PR = SM_FT+4*FT_WG;
__device__ __forceinline__ uint32_t tb_off(int ch){ return SM_TB+(ch<3? ch : 7-ch)*8192; }
__device__ __forceinline__ uint32_t kg_off(int wg){ return wg<3? SM_KG+wg*KG_WG : SM_XS-8192; }
constexpr int PLN = 1184, UB = 4*PLN, FPL = 288, FB = 32*FPL, UF = UB+FB;
static_assert(SM_PR%16==0 && SM_PR+5184 <= SM_QS, "front smem");
static_assert(2*UB+2*FB <= KG_WG, "kg alias");

#define TS(k)
#define TSP(k,p)
constexpr int SM_ALLOC = SM_TOTAL;

struct Params {
  const bf16 *in[8];
  const bf16 *x;
  Scratch* s;
  const bf16 *wgp, *wup, *wdp;
  uint32_t zero;
  CUtensorMap wm, xns, xts, x1red, wg, wu, wps, x1a, x1r, out;
};
__device__ __forceinline__ uint32_t cpz(uint32_t v, uint32_t z){ uint32_t r; asm volatile("xor.b32 %0,%1,%2;":"=r"(r):"r"(v),"r"(z)); return r; }

struct KA { uint32_t er[4], ei[4], hr[4], hi[4], ar[2], ai[2], mH1, m2, m4, m6, m32, m64, mH8; float last, os, dsk; };
__device__ __forceinline__ void kgen_a(KA& k, uint32_t sb, int tl, int ch, int dw){
  const uint32_t pr=sb+SM_PR+ch*256;
  const float la=bf_lo(lds16(pr+tl*2)), ldt=bf_lo(lds16(sb+SM_PR+5120+dw*2)), aim=bf_lo(lds16(pr+1280+tl*2));
  const uint2 ma=lds64(pr+2560+(tl&31)*8), mb=lds64(pr+3840+(tl&31)*8);
  cf C; C.x=bf_lo(lds16(pr+2560+tl*2)); C.y=bf_lo(lds16(pr+3840+tl*2));
  k.dsk=bf_lo(lds16(sb+SM_PR+5152+dw*2));
  const float dt=bfr(expf(ldt));
  const float l2=bfr(expf(la))*dt*-1.4426950408889634f, tn=aim*dt*0.15915494309189535f;
  uint32_t ex=__vmaxu2(__vmaxu2(ma.x&0x7fff7fffu,ma.y&0x7fff7fffu),__vmaxu2(mb.x&0x7fff7fffu,mb.y&0x7fff7fffu));
  ex=__reduce_max_sync(~0u,max(ex&0xffffu,ex>>16)); ex=min(max(ex>>7,1u),253u);
  { const float sc=__uint_as_float((254u-ex)<<23); C.x*=sc; C.y*=sc; }
  k.os=2.f*dt*__uint_as_float(ex<<23);
  cf E1=cexp_dir(l2,tn), H1=cexp_dir(l2*128.f,tn*128.f);
  cf H2=csq(H1), H4=csq(H2), H8=csq(H4), H16=csq(H8);
  float last=fmaf(C.x,H16.x,-C.y*H16.y);
  last+=__shfl_xor_sync(~0u,last,16);
  cf E2=csq(E1), E3=cmul(E2,E1), E4=csq(E2), E5=cmul(E4,E1), E6=csq(E3), E7=cmul(E4,E3);
  k.er[0]=pack_h2(1.f,E1.x); k.er[1]=pack_h2(E2.x,E3.x); k.er[2]=pack_h2(E4.x,E5.x); k.er[3]=pack_h2(E6.x,E7.x);
  k.ei[0]=pack_h2(0.f,E1.y); k.ei[1]=pack_h2(E2.y,E3.y); k.ei[2]=pack_h2(E4.y,E5.y); k.ei[3]=pack_h2(E6.y,E7.y);
  k.mH1=pack_h2(H1.x,H1.y); k.m2=pack_h2(E2.x,E2.y); k.m4=pack_h2(E4.x,E4.y); k.m6=pack_h2(E6.x,E6.y); k.mH8=pack_h2(H8.x,H8.y);
  last+=__shfl_xor_sync(~0u,last,8);
  {
    cf E8=csq(E4); E8.y=-E8.y; cf a0; a0.x=C.x; a0.y=-C.y;
    cf E16=csq(E8), a1=cmul(a0,E8), a2=cmul(a0,E16), a3=cmul(a1,E16), E32=csq(E16), E64=csq(E32);
    k.ar[0]=pack_h2(a0.x,a1.x); k.ar[1]=pack_h2(a2.x,a3.x); k.ai[0]=pack_h2(a0.y,a1.y); k.ai[1]=pack_h2(a2.y,a3.y);
    k.m32=pack_h2(E32.x,E32.y); k.m64=pack_h2(E64.x,E64.y); }
  last+=__shfl_xor_sync(~0u,last,4);
  cf H3=cmul(H2,H1), H5=cmul(H4,H1), H6=csq(H3), H7=cmul(H4,H3);
  k.hr[0]=pack_h2(1.f,H1.x); k.hr[1]=pack_h2(H2.x,H3.x); k.hr[2]=pack_h2(H4.x,H5.x); k.hr[3]=pack_h2(H6.x,H7.x);
  k.hi[0]=pack_h2(0.f,H1.y); k.hi[1]=pack_h2(H2.y,H3.y); k.hi[2]=pack_h2(H4.y,H5.y); k.hi[3]=pack_h2(H6.y,H7.y);
  k.last=last;
}
__device__ __forceinline__ void kgen_b(const KA& k, uint32_t sb, int wg, int warp, int lane){
  const int tl=warp*32+lane;
  const uint32_t wb=sb+kg_off(wg), sa=wb+tl*16;
  const uint32_t lp=sb+SM_FT+wg*FT_WG+1552;
  { uint32_t a0,a1,a2,a3,b0,b1,b2,b3;
    sts128(sa,k.er[0],k.er[1],k.er[2],k.er[3]); sts128(sa+2048,k.ei[0],k.ei[1],k.ei[2],k.ei[3]);
    hmulc(k.er[0],k.ei[0],k.mH1,a0,b0); hmulc(k.er[1],k.ei[1],k.mH1,a1,b1); hmulc(k.er[2],k.ei[2],k.mH1,a2,b2); hmulc(k.er[3],k.ei[3],k.mH1,a3,b3);
    sts128(sa+2*2048,a0,a1,a2,a3); sts128(sa+3*2048,b0,b1,b2,b3); }
  { uint32_t r2,r3,i2,i3,c0,c1,c2,c3,b0,b1,b2,b3;
    hmulc(k.ar[0],k.ai[0],k.m32,r2,i2); hmulc(k.ar[1],k.ai[1],k.m32,r3,i3);
    sts128(sa+10*2048,k.ar[0],k.ar[1],r2,r3); sts128(sa+11*2048,k.ai[0],k.ai[1],i2,i3);
    hmulc(k.ar[0],k.ai[0],k.m64,c0,b0); hmulc(k.ar[1],k.ai[1],k.m64,c1,b1); hmulc(r2,i2,k.m64,c2,b2); hmulc(r3,i3,k.m64,c3,b3);
    sts128(sa+12*2048,c0,c1,c2,c3); sts128(sa+13*2048,b0,b1,b2,b3); }
  { uint32_t a,b,c,e,f,g;
    hmulc(k.hr[1],k.hi[1],k.m2,a,b); hmulc(k.hr[1],k.hi[1],k.m4,c,e); hmulc(k.hr[1],k.hi[1],k.m6,f,g);
    sts128(sa+4*2048,k.hr[1],a,c,f); sts128(sa+5*2048,k.hi[1],b,e,g); }
  { uint32_t a,b,c,e;
    hmulc(k.hr[2],k.hi[2],k.m4,a,b); hmulc(k.hr[3],k.hi[3],k.m4,c,e);
    sts128(sa+6*2048,k.hr[2],k.hr[3],a,c); sts128(sa+7*2048,k.hi[2],k.hi[3],b,e); }
  { uint32_t c0,c1,c2,c3,b0,b1,b2,b3;
    hmulc(k.hr[0],k.hi[0],k.mH8,c0,b0); hmulc(k.hr[1],k.hi[1],k.mH8,c1,b1); hmulc(k.hr[2],k.hi[2],k.mH8,c2,b2); hmulc(k.hr[3],k.hi[3],k.mH8,c3,b3);
    sts128(sa+8*2048,c0,c1,c2,c3); sts128(sa+9*2048,b0,b1,b2,b3); }
  if(lane<4) sts32f(lp+(warp*4+lane)*4,k.last);
  fence_async_smem();
}
template<bool NEXT> __device__ __forceinline__ void kgen_c(KA& k, uint32_t sb, uint32_t t0, int wg, int warp, int lane, int ch, int d, int dw, uint32_t zr, int bid, int bn){
  const float os=k.os, dsk=k.dsk;
  const int tl=warp*32+lane;
  const uint32_t wb=sb+kg_off(wg);
  const uint32_t ft=sb+SM_FT+wg*FT_WG+4, R3=ft+1036, lp=R3+512;
  float acc[8];
  { const uint64_t da=mkdesc(wb+(ch&zr),2048,4096,0), db=da+10*128;
    wg_fence();
    #pragma unroll
    for(int o=0;o<16;o++) wgmma_n16_f16(acc,da+8*o,db+8*o,o>0);
    wg_commit(); }
  const int g=lane>>2, t=lane&3;
  if(warp==3){ if(lane==0){ float4 x=lds128f(lp), y=lds128f(lp+16), z=lds128f(lp+32), w=lds128f(lp+48);
      float s=os*((((x.x+x.y)+(x.z+x.w))+((y.x+y.y)+(y.z+y.w)))+(((z.x+z.y)+(z.z+z.w))+((w.x+w.y)+(w.z+w.w))));
      sts16(R3+3*128,bf_bits(s)); sts32(ft-4,0); }
    if(lane<16) sts32(R3+(lane>>2)*128+64+(lane&3)*4,0); }
  if(NEXT){ if(wg==0) kgen_a(k,sb,tl,4,dw+4); }
  wg_wait<0>(); reg_fence(acc);
  if(warp<2){
    const int b0= warp? 256+64*(g&1)+(g>>1) : g, b1= warp? 384+32*(g&3)+(g>>2) : 128+g, s0= warp? 4:8, s1= warp? 2:8;
    #pragma unroll
    for(int i=0;i<8;i++){ const int n=8*(i>>2)+2*t+(i&1), idx=(i&2)? b1+s1*n : b0+s0*n; float v=acc[i]*os;
      if(i==0 && tl==0) v+=dsk;
      sts16(ft+idx*2,bf_bits(v)); }
  } else if(warp==2){
    #pragma unroll
    for(int i=0;i<4;i++){ const int mm=16*g+8*(i>>1)+2*t+(i&1)-1; float v=acc[(i>>1)*4+(i&1)]*os;
      sts16(mm<0? ft+1024 : R3+(mm&3)*128+(31-(mm>>2))*2, bf_bits(v)); }
  }
  bar_sync(bid,bn);
  const uint32_t P=sb+tb_off(ch)+256, T3=P+4672;
  { const uint32_t ta=R3+warp*128+(lane>>1)*4, sh=(lane&1)*16;
    uint32_t a0=lds32(ft+tl*4), a1=lds32(ft+tl*4-4), c0=lds32(ft+512+tl*4), c1=lds32(ft+516+tl*4), e=lds16(ft+1024);
    uint32_t v0=lds32(ta), v1=lds32(ta+4), v2=lds32(ta+8), v3=lds32(ta+12), v4=lds32(ta+16);
    uint32_t pm=0; if(tl==0) pm=lds32(ft+508);
    sts64(P+tl*8, prmt(a0,a1,0x7610), prmt(a0,a0,0x1032));
    const uint32_t ll=prmt(c0,c0,0x1010), hl=prmt(c0,c0,0x1032), nh=prmt(c0,c1,0x3254);
    if(warp<2) sts128(P+1024+tl*16, tl? ll : prmt(c0,pm,0x7610), ll, hl, nh);
    else { const uint32_t hh=prmt(c0,c0,0x3232), nn=prmt(c1,c1,0x1010);
      sts128(P+tl*32, ll,ll,ll,hl); sts128(P+tl*32+16, hh,hh,nh,nn); }
    sts32(P+4096+tl*4, tl<5? (e|(e<<16)) : (tl==5? e<<16 : 0u));
    if(tl<64){ sts32(P-256+tl*4,0); sts128(T3+(tl>>4)*768+512+(tl&15)*16,0,0,0,0); }
    sts128(T3+warp*768+lane*16, __funnelshift_r(v0,v1,sh), __funnelshift_r(v1,v2,sh), __funnelshift_r(v2,v3,sh), __funnelshift_r(v3,v4,sh));
  }
}

template<int NS> __device__ __forceinline__ void conv_load(uint32_t (&v)[17], uint32_t pp){
  #pragma unroll
  for(int i=0;i<2*NS+1;i++) v[i]=lds32(pp+(i-1)*32);
}
template<int N,int NS> __device__ __forceinline__ void conv_issue(float (&c)[32], const uint32_t (&w)[17], uint64_t db, int acc, uint32_t zr){
  uint32_t v[2*NS+1];
  #pragma unroll
  for(int i=0;i<2*NS+1;i++) v[i]= V4? cpz(w[i],zr) : w[i];
  wg_fence();
  #pragma unroll
  for(int i=0;i<NS;i++){ const int o=(2-2*(i&1))*(PLN/16)+(i>>1);
    if constexpr(N==64) wgmma_n64_rs(c, v[2*i+1],v[2*i+2],v[2*i],v[2*i+1], db+o, i>0 || acc);
    else if constexpr(N==48) wgmma_n48_rs(c, v[2*i+1],v[2*i+2],v[2*i],v[2*i+1], db+o, 1);
    else wgmma_n32_rs(c, v[2*i+1],v[2*i+2],v[2*i],v[2*i+1], db+o, 1); }
}
__device__ __forceinline__ void rx_store(uint32_t sb, const bf16* inbox, int ch, uint32_t TG, uint32_t U, int tl, uint32_t t0){
  const int o=(tl>>1)*160+ch*32+(tl&1)*16;
  uint4 v[2]={lds128(sb+SM_XR+o), lds128(sb+SM_XR+10240+o)};
  const uint2 sc=lds64(sb+SM_MI+5152+ch*8);
  while(true){
    #pragma unroll
    for(int q=0;q<2;q++){ v[q].x^=TG; v[q].y^=TG; v[q].z^=TG; v[q].w^=TG; }
    if(!__any_sync(~0u,(v[0].x|v[0].y|v[0].z|v[0].w|v[1].x|v[1].y|v[1].z|v[1].w)&0x40004000u)) break;
    if(__any_sync(~0u,(int)(clk32()-t0)<0)) break;
    #pragma unroll
    for(int q=0;q<2;q++) asm volatile("ld.relaxed.gpu.global.v4.u32 {%0,%1,%2,%3}, [%4];":"=r"(v[q].x),"=r"(v[q].y),"=r"(v[q].z),"=r"(v[q].w):"l"((const unsigned char*)inbox+o+q*10240):"memory"); }
  #pragma unroll
  for(int q=0;q<2;q++) sts128(U+(tl&3)*PLN+(63-32*q-(tl>>2))*16, bf2_add(bf2_mul(v[q].x,sc.x),sc.y), bf2_add(bf2_mul(v[q].y,sc.x),sc.y), bf2_add(bf2_mul(v[q].z,sc.x),sc.y), bf2_add(bf2_mul(v[q].w,sc.x),sc.y));
}
__device__ __forceinline__ void box_filter(uint32_t U, int tl){
  const uint32_t Fb=U+UB; const int q0=tl+2, q1=tl+3, q2=tl+4;
  uint2 lo=lds64(U+(q0&3)*PLN+(64-(q0>>2))*16+8); uint4 mid=lds128(U+(q1&3)*PLN+(64-(q1>>2))*16); uint2 hi=lds64(U+(q2&3)*PLN+(64-(q2>>2))*16);
  uint32_t w[8]={lo.x,lo.y,mid.x,mid.y,mid.z,mid.w,hi.x,hi.y}; float u[16];
  #pragma unroll
  for(int i=0;i<8;i++){ u[2*i]=bf_lo(w[i]); u[2*i+1]=bf_hi(w[i]); }
  float s7[8], s9[8];
  s7[0]=((u[1]+u[2])+(u[3]+u[4]))+((u[5]+u[6])+u[7]);
  #pragma unroll
  for(int i=1;i<8;i++) s7[i]=s7[i-1]+(u[i+7]-u[i]);
  #pragma unroll
  for(int i=0;i<8;i++) s9[i]=s7[i]+(u[i]+u[i+8]);
  const uint32_t a[8]={pack_bf16(s7[0],s7[1]),pack_bf16(s7[2],s7[3]),pack_bf16(s7[4],s7[5]),pack_bf16(s7[6],s7[7]),
                       pack_bf16(s9[0],s9[1]),pack_bf16(s9[2],s9[3]),pack_bf16(s9[4],s9[5]),pack_bf16(s9[6],s9[7])};
  #pragma unroll
  for(int c=0;c<4;c++){ const int q=tl+c;
    if(q<128) sts128(Fb+(c*8+((q>>3)&4)+(q&3))*FPL+((q>>6)*8+((q>>2)&7))*16, a[4*(c&1)],a[4*(c&1)+1],a[4*(c&1)+2],a[4*(c&1)+3]); }
}

__device__ __forceinline__ void mod_gemv(const Params& p, uint32_t sb, int cta, int wg, int warp, int lane, uint32_t tag16, uint32_t t0){
      const uint32_t MI=sb+SM_MI, wmb=sb+SM_BAR+176; const int g=lane>>2, t=lane&3, mi=lane>>3, lead=(warp|lane)==0; (void)lead;
      const uint32_t toff=warp*10240+((mi>>1)*8+(lane&7))*64, tsw=(lane>>1)&3;
      uint32_t bv[20];
      #pragma unroll
      for(int k=0;k<20;k++) bv[k]=lds32(MI+(warp*160+k*8+2*t)*2);
      mbar_wait(wmb,0,t0);
      TSP(15,lead);
      float c0[4]={0,0,0,0}, c1[4]={0,0,0,0};
      { float e0[4]={0,0,0,0}, e1[4]={0,0,0,0};
        #pragma unroll
        for(int hf=0;hf<2;hf++){ uint32_t a[40];
          #pragma unroll
          for(int k=0;k<5;k++){ uint32_t ad=sb+SM_WM+toff+(hf*5+k)*1024;
            ldsm4t(ad+(((mi&1)^tsw)<<4),a[8*k],a[8*k+1],a[8*k+2],a[8*k+3]); ldsm4t(ad+(((2+(mi&1))^tsw)<<4),a[8*k+4],a[8*k+5],a[8*k+6],a[8*k+7]); }
          #pragma unroll
          for(int k=0;k<5;k++){ const int kk=hf*5+k;
            if(kk&1){ mma_bf16(e0,a[8*k],a[8*k+1],a[8*k+2],a[8*k+3],bv[2*kk],bv[2*kk+1]); mma_bf16(e1,a[8*k+4],a[8*k+5],a[8*k+6],a[8*k+7],bv[2*kk],bv[2*kk+1]); }
            else { mma_bf16(c0,a[8*k],a[8*k+1],a[8*k+2],a[8*k+3],bv[2*kk],bv[2*kk+1]); mma_bf16(c1,a[8*k+4],a[8*k+5],a[8*k+6],a[8*k+7],bv[2*kk],bv[2*kk+1]); } } }
        c0[0]+=e0[0]; c0[2]+=e0[2]; c1[0]+=e1[0]; c1[2]+=e1[2]; }
      if(t==0){ uint32_t a=MI+2560+warp*128+g*4; sts32f(a,c0[0]); sts32f(a+32,c0[2]); sts32f(a+64,c1[0]); sts32f(a+96,c1[2]); }
      bar_sync(1+wg,128);
      if(warp==1){ uint32_t a=MI+2560+lane*4; float s=(lds32f(a)+lds32f(a+128))+(lds32f(a+256)+lds32f(a+384));
        asm volatile("st.relaxed.gpu.global.u32 [%0], %1;"::"l"(p.s->mod+cta*32+lane),"r"((bf_bits(s)<<16)|tag16):"memory"); }
      TSP(16,warp==1 && lane==0);
}

__device__ __forceinline__ void fetch_inbox(const Params& p, uint32_t sb, int cta, int lane, unsigned ep, uint32_t tag16, uint32_t t0){
  const uint32_t gateb=sb+SM_BAR+224;
  while(__any_sync(~0u,(int)(ld_relaxed(p.s->cnt+96)-(ep+1)*128u)<0 && (int)(clk32()-t0)>=0)) __nanosleep(20);
  if(elect_one()){
    mbar_wait(sb+SM_BAR+216,0,t0);
    TS(78);
    fence_async_global(); mbar_expect_tx(gateb,20480); bulk_g2s(sb+SM_XR,p.s->inbox+(size_t)cta*128*80,20480,gateb); }
  __syncwarp();
  { const unsigned* mp=p.s->mod+((lane&1)^1)*D_+5*cta+min(lane>>1,4);
    uint32_t v=ld_relaxed(mp)^tag16;
    while(__any_sync(~0u,(v&0xffffu) && (int)(clk32()-t0)>=0)){ __nanosleep(40); v=ld_relaxed(mp)^tag16; }
    const float cs=bfr(1.f+__uint_as_float(v))*4294967296.f;
    v=(lane&1)? v|(v>>16) : pack_bf16(cs,cs);
    if(lane<10) sts32(sb+SM_MI+5152+lane*4,v); }
  __syncwarp(); mbar_arrive_pred(gateb,1,lane==0);
}

template<int PACE> __device__ __forceinline__ void geglu(float (&acc0)[72], float (&acc1)[72], uint32_t sb, int sub, int warp, int lane, uint32_t zr){
  const int g=lane>>2, t=lane&3;
  float2 stt[4];
  #pragma unroll
  for(int r=0;r<4;r++) stt[r]=lds64f(sb+SM_ST+((r>>1)*64+warp*16+(r&1)*8+g)*8);
  const uint32_t qa=sb+SM_QS+(sub*72+2*t)*16;
  const uint32_t ga=sb+SM_GS+(((lane>>4)*64)+warp*16+((lane>>3)&1)*8+(lane&7))*16;
  float4 q0, q1, n0, n1;
  if(PACE==0 || PACE==5){ q0=lds128f(qa); q1=lds128f(qa+16); }
  #pragma unroll
  for(int i=0;i<9;i++){
    if(PACE==0 || PACE==5){ if(i<8){ n0=lds128f(qa+i*128+128); n1=lds128f(qa+i*128+144); } }
    else { q0=lds128f(qa+i*128); q1=lds128f(qa+i*128+16); }
    uint32_t o[4];
    #pragma unroll
    for(int r=0;r<4;r++){
      float res[2];
      #pragma unroll
      for(int e=0;e<2;e++){
        float4 q = e? q1:q0;
        float ag = (r>>1)? acc1[8*i+(r&1)*2+e] : acc0[8*i+(r&1)*2+e];
        float au = (r>>1)? acc1[8*i+4+(r&1)*2+e] : acc0[8*i+4+(r&1)*2+e];
        float gv = fmaf(stt[r].x, ag, fmaf(stt[r].y,q.x,q.y));
        float uv = fmaf(0.5f*stt[r].x, au, fmaf(stt[r].y,q.z,q.w));
        float z = gv*fmaf(gv*gv, 0.044715f*0.7978845608f, 0.7978845608f);
        float pr = gv*uv;
        res[e] = fmaf(pr, tanh_fast(z), pr);
      }
      o[r]=pack_bf16(res[0],res[1]);
      if(PACE==3) stt[(r+1)&3].y=__uint_as_float(__float_as_uint(stt[(r+1)&3].y)|(o[r]&zr));
      if((PACE==4 || PACE==5) && (r&1)){ stt[(r+1)&3].y=__uint_as_float(__float_as_uint(stt[(r+1)&3].y)|(o[r-1]&zr)); stt[(r+2)&3].y=__uint_as_float(__float_as_uint(stt[(r+2)&3].y)|(o[r]&zr)); }
    }
    stsm4(ga+i*2048,o[0],o[1],o[2],o[3]);
    if(PACE==0 || PACE==5){ q0=n0; q1=n1; }
    if(i==4){ fence_async_smem(); bar_arrive(11,160); }
  }
}

template<bool BYSM> __global__ void __launch_bounds__(512,1) fused_kernel(const __grid_constant__ Params p){
  extern __shared__ __align__(1024) unsigned char smem[];
  const uint32_t sb = opaque(smem_u32(smem));
  const uint32_t t0 = clk32();
  const int tid=threadIdx.x, lane=tid&31, tl=tid&127;
  const int wid=__shfl_sync(~0u,tid>>5,0), wg=wid>>2, warp=wid&3;
  int cta;
  if(BYSM){ asm volatile("mov.u32 %0, %%smid;":"=r"(cta)); cta= cta<120? cta : cta<124? cta+8 : cta-4; } else cta=blockIdx.x;
  if(cta>=128){
    const uint32_t bar=sb+SM_BAR; const int e=cta-128, n=(54-e+3)>>2;
    const unsigned char* src=(const unsigned char*)p.wdp+e*40960;
    __nanosleep(1500);
    if(wid==0){ if(elect_one()){
      #pragma unroll 1
      for(int i=0;i<3;i++){ mbar_init(bar+8*i,1); mbar_expect_tx(bar+8*i,40960); bulk_g2s(sb+i*40960,src+(size_t)i*163840,40960,bar+8*i); } }
      __syncwarp(); }
    __syncthreads();
    int s=0, ph=0;
    #pragma unroll 1
    for(int i=0;i<n;i++){
      mbar_wait(bar+8*s,ph,t0);
      const uint32_t ob=sb+122880+(i&1)*40960; uint4 v[5];
      #pragma unroll
      for(int k=0;k<5;k++){ const int u=(tid>>3)+64*k, kb=u/80, c=((u%80)&~7)+((u+lane)&7); v[k]=lds128(sb+s*40960+kb*10240+(lane&7)*1280+c*16); }
      if(wid==0){ if(elect_one()) asm volatile("cp.async.bulk.wait_group.read 1;":::"memory"); __syncwarp(); }
      __syncthreads();
      #pragma unroll
      for(int k=0;k<5;k++){ const int u=(tid>>3)+64*k, kb=u/80, c=((u%80)&~7)+((u+lane)&7); sts128(ob+(c/10)*5120+kb*1280+(c%10)*128+(lane&7)*16,v[k].x,v[k].y,v[k].z,v[k].w); }
      fence_async_smem();
      __syncthreads();
      if(wid==0){ if(elect_one()){
        if(i+3<n){ mbar_expect_tx(bar+8*s,40960); bulk_g2s(sb+s*40960,src+(size_t)(i+3)*163840,40960,bar+8*s); }
        #pragma unroll 1
        for(int jj=0;jj<8;jj++) bulk_s2g((unsigned char*)p.s->W2p+(size_t)jj*276480+(i*4+e)*5120,ob+jj*5120,5120);
        bulk_commit(); }
        __syncwarp(); }
      if(++s==3){ s=0; ph^=1; } }
    if(wid==0){ if(elect_one()){ bulk_wait0(); red_relaxed(p.s->cnt+64); } __syncwarp(); }
    return; }
  const int g=lane>>2, t=lane&3;
  const int lead = tl==0;
  const uint32_t fullb=sb+SM_BAR, emptyb=fullb+64, gsb=fullb+128, depb=fullb+136, xb=fullb+168, wmb=fullb+176, w1b=fullb+184, w2b=fullb+192, gateb=fullb+224, gbb=fullb+232, prb=fullb+240, cb_=fullb+200, fb_=fullb+48, full2=fullb+256, empty2=fullb+320, resb=fullb+312, stb=fullb+376;
  const uint32_t MI=sb+SM_MI;
  const int w0=min((cta*5)&~7,D_-16), dw=5*cta-w0;
  if(wid<3){ if(elect_one()){
    if(wid<2){ const uint32_t bar=prb+8*wid; mbar_init(bar,1); mbar_expect_tx(bar,2592);
      bulk_g2s(sb+SM_PR+wid*2560,(wid? p.in[2]:p.in[0])+cta*5*N_,1280,bar); bulk_g2s(sb+SM_PR+wid*2560+1280,(wid? p.in[3]:p.in[1])+cta*5*N_,1280,bar);
      bulk_g2s(sb+SM_PR+5120+wid*32,(wid? p.in[5]:p.in[4])+w0,32,bar); }
    else { mbar_init(xb,2); mbar_init(wmb,1); mbar_init(gateb,2); mbar_init(gbb,1); mbar_init(cb_,1); mbar_init(fb_,1); mbar_init(fb_+8,1); mbar_init(fullb+216,1);
      mbar_expect_tx(xb,20480); mbar_expect_tx(wmb,40960); mbar_expect_tx(cb_,1280); }
    } __syncwarp(); }
  __syncthreads();
  if(wid>=8){ if(elect_one()){
    const bf16* src=p.x+(size_t)(cta*16+(wid-8)*2)*D_; const uint32_t dst=sb+SM_XR+(wid-8)*2592;
    if(X_DELAY){ const uint32_t t1=clk32(); while((int)(clk32()-t1) < X_DELAY); }
    if(wid==12) bulk_g2s(MI+1280,p.in[6],1280,cb_);
    bulk_g2s(dst,src,1280,xb); bulk_g2s(dst+1296,src+D_,1280,xb);
    if(wid==13){ prefetch_tmap(&p.wm); prefetch_tmap(&p.xns); prefetch_tmap(&p.xts);
      }
    else if(wid==14){
      for(int i=0;i<NSTG;i++){ mbar_init(fullb+8*i,1); mbar_init(emptyb+8*i,5); }
      mbar_init(gsb,1); for(int i=0;i<4;i++) mbar_init(depb+8*i,1);
      mbar_init(emptyb+48,1); mbar_init(emptyb+56,1); mbar_init(stb,1);
      mbar_init(w1b,1); mbar_init(resb,1);
      for(int i=0;i<NST2;i++){ mbar_init(full2+8*i,1); mbar_init(empty2+8*i,1); }
    } else if(wid==15){ sts32(fullb+208,ld_relaxed(p.s->cnt)); mbar_arrive_pred(xb,1,1); }
    } __syncwarp(); }
  KA ka; uint32_t xv[20];
  TSP(82,tid==96);
  mbar_wait(prb,0,t0); mbar_wait(prb+8,0,t0);
  TSP(1,tid==96);
  if(wid==5 && cta<40){ if(elect_one()){
    #pragma unroll
    for(int i=0;i<4;i++) tma_ld2(sb+SM_WM+i*10240,&p.wm,cta*32,i*160,wmb);
    } __syncwarp(); }
  kgen_a(ka,sb,tl,wg,dw+wg);
  if(B23 || wg<2) kgen_b(ka,sb,wg,warp,lane);
  TSP(60,tid==0);
  if(wid==5 && cta>=40 && cta<120){ if(elect_one()){
    #pragma unroll
    for(int i=0;i<4;i++) tma_ld2(sb+SM_WM+i*10240,&p.wm,cta*32,i*160,wmb);
    } __syncwarp(); }
  if(wg<2){
    if(GATE==2) bar_sync(15,512); else bar_sync(1+wg,128);
    kgen_c<true>(ka,sb,t0,wg,warp,lane,wg,5*cta+wg,dw,p.zero,1+wg,128); TSP(2,tid==0);
    mbar_wait(xb,0,t0);
  } else {
    mbar_wait(xb,0,t0);
    TSP(13,tid==384);
    const int w8=wid-8;
    const uint32_t xa=sb+SM_XR+(lane&15)*1296+(w8*80+(lane>>4)*8)*2;
    #pragma unroll
    for(int k=0;k<5;k++) ldsm4(xa+k*32,xv[4*k],xv[4*k+1],xv[4*k+2],xv[4*k+3]);
    const uint32_t tg2=(lds32(fullb+208)>>9)%3u+1;
    const int chl=w8*80+(lane>>4)*8+(lane&7), hh=(lane>>3)&1;
    const uint32_t na=sb+SM_XR+chl*32+hh*16;
    { float c1[4]={0,0,0,0}, c2[4]={0,0,0,0}, c3[4]={0,0,0,0};
      #pragma unroll
      for(int k=0;k<5;k++){ const uint32_t* a=xv+4*k;
        mma_bf16(c1,a[0],a[1],a[2],a[3],a[0],a[2]); mma_bf16(c2,a[0],a[1],a[2],a[3],a[1],a[3]); mma_bf16(c3,a[0],a[1],a[2],a[3],0x3f803f80u,0x3f803f80u); }
      if(t==(g>>1)) sts128f(MI+3840+w8*128+g*16, make_float4(c3[0],(g&1)?c1[1]:c1[0],c3[2],(g&1)?c2[3]:c2[2])); }
    TSP(86,tid==384);
    bar_sync(13,256);
    uint32_t nm[2], r2h[2], r2l[2];
    { float4 q0=lds128f(MI+3840+t*256+g*16), q1=lds128f(MI+3840+t*256+128+g*16);
      float a=q0.x+q1.x, b=q0.y+q1.y, c=q0.z+q1.z, e=q0.w+q1.w;
      float su=((t&2)?c:a)+__shfl_xor_sync(~0u,(t&2)?a:c,2), sq=((t&2)?e:b)+__shfl_xor_sync(~0u,(t&2)?b:e,2);
      su+=__shfl_xor_sync(~0u,su,1); sq+=__shfl_xor_sync(~0u,sq,1);
      const float mu=su*(1.f/D_), var=bfr(fmaxf(sq*(1.f/D_)-mu*mu,0.f));
      const float rr=__fdividef(2.3283064365386963e-10f,bfr(sqrt_fast(bfr(var+1e-5f))));
      const uint32_t w1=pack_bf16(-mu,rr), w2=pack_bf16(rr-bf_hi(w1),0.f);
      const uint32_t o1=__shfl_xor_sync(~0u,w1,2), o2=__shfl_xor_sync(~0u,w2,2);
      const uint32_t a1=(t&2)?o1:w1, a2=(t&2)?o2:w2, b1=(t&2)?w1:o1, b2=(t&2)?w2:o2;
      nm[0]=prmt(a1,a1,0x1010); r2h[0]=prmt(a1,a1,0x3232); r2l[0]=prmt(a2,a2,0x1010);
      nm[1]=prmt(b1,b1,0x1010); r2h[1]=prmt(b1,b1,0x3232); r2l[1]=prmt(b2,b2,0x1010); }
    const uint32_t TT=((tg2>>(g&1))&1)*0x40004000u;
    #pragma unroll
    for(int k=0;k<5;k++){ uint32_t o[4];
      #pragma unroll
      for(int i=0;i<4;i++){ uint32_t dd=bf2_add(xv[4*k+i],nm[i&1]); o[i]=bf2_fma(dd,r2h[i&1],bf2_mul(dd,r2l[i&1]))|TT; }
      stsm4t(na+k*512,o[0],o[1],o[2],o[3]); }
    fence_async_smem();
    if(wg==2) bar_arrive(14,256); else bar_sync(14,256);
    if(wid==12){ if(elect_one()){ tma_st2(&p.xns,cta*80,0,sb+SM_XR); bulk_commit();
      red_relaxed(p.s->cnt+96);
      TS(14); } __syncwarp(); }
    if(GATE==2) bar_arrive(15,512); else if(GATE==1) bar_arrive(15,384);
    if(wid==12){ if(elect_one()){ bulk_wait0_read(); mbar_arrive_pred(fullb+216,1,1); } __syncwarp(); }
  }
  const int mi=lane>>3;
  const uint32_t toff=warp*10240+((mi>>1)*8+(lane&7))*64, tsw=(lane>>1)&3;
  const unsigned cnt0=lds32(fullb+208), ep=cnt0>>9; const uint32_t tag16=ep%65535u+1;
  const int wsl= cta<100? cta : cta>=120? cta-20 : -1, mat=wsl>=54, sl=wsl-54*mat;
  const uint32_t kb=sb+SM_KG+wg*KG_WG;
  if(wg==1){
    { mbar_wait(cb_,0,t0);
      uint32_t cv[5];
      #pragma unroll
      for(int i=0;i<5;i++) cv[i]=lds16(MI+1280+(warp*160+lane+32*i)*2);
      #pragma unroll
      for(int i=0;i<5;i++){ float x=bf_lo(cv[i]); sts16(MI+(warp*160+lane+32*i)*2, bf_bits(__fdividef(x,1.f+__expf(-x)))); }
      __syncwarp(); }
    TSP(77,lead);
    if(cta>=40 && warp==0) fetch_inbox(p,sb,cta,lane,ep,tag16,t0);
    if(cta<120) mod_gemv(p,sb,cta,wg,warp,lane,tag16,t0);
    if(cta<40 && warp==0) fetch_inbox(p,sb,cta,lane,ep,tag16,t0);
  } else {
    if(wg==0 && GATE==1) bar_sync(15,384);
    if(wg==0 || !B23){ kgen_b(ka,sb,wg,warp,lane); bar_sync(1+wg,128); }
    const int ch= wg? wg : 4;
    kgen_c<false>(ka,sb,t0,wg,warp,lane,ch,5*cta+ch,0,p.zero,wg? 13:1,wg? 256:128); TSP(3,tid==0); TSP(76,tid==256);
    if(wg){
      const int chl=(wid-8)*80+(lane>>4)*8+(lane&7);
      const uint32_t ra=sb+SM_XS+chl*32+((((lane>>3)^(chl>>2))&1)<<4);
      #pragma unroll
      for(int k=0;k<5;k++) stsm4t(ra+k*512,xv[4*k],xv[4*k+1],xv[4*k+2],xv[4*k+3]);
      fence_async_smem();
      if(wg==2) bar_arrive(14,256); else bar_sync(14,256); }
  }
  uint32_t mv[10];
  { const bf16* inbox=p.s->inbox+(size_t)cta*128*80;
    const uint32_t tg2=ep%3u+1, TG=((tg2&1)<<14)|((tg2>>1)<<30);
    if(wg<3){
      if(tl<56){ uint32_t a= tl<40? kb+(tl&3)*PLN+(64+(tl>>2))*16 : kb+UB+(((tl-40)>>2)*8+(tl&3))*FPL; sts128(a,0,0,0,0); if(wg<2) sts128(a+UF,0,0,0,0); }
      mbar_wait(gateb,0,t0);
      TSP(83,tid==0);
      rx_store(sb,inbox,wg,TG,kb,tl,t0);
      fence_async_smem();
      bar_arrive(12,512);
      if(wg<2){ bar_arrive(9,384); bar_sync(1+wg,128); } else bar_sync(9,384);
      TSP(4,tid==0); TSP(12,tid==128);
    } else {
      if(warp==0){ if(elect_one()){
        mbar_wait(gateb,0,t0);
        #pragma unroll 1
        for(int i=0;i<4;i++) tma_st2(&p.xts,cta*16,i*160,sb+SM_XS+i*5120);
        bulk_commit();
        } __syncwarp(); }
      bar_sync(12,512);
      if(warp==2 && wsl>=0){ if(elect_one()){ mbar_expect_tx(w1b,40960);
        #pragma unroll 1
        for(int i=0;i<4;i++) tma_ld2(sb+SM_WM+i*10240,mat?&p.wu:&p.wg,sl*32,i*160,w1b);
        } __syncwarp(); }
      rx_store(sb,inbox,3,TG,sb+SM_KG+UF,tl,t0); rx_store(sb,inbox,4,TG,sb+SM_KG+KG_WG+UF,tl,t0);
      if(warp==0){ if(elect_one()){ bulk_wait0(); red_relaxed(p.s->cnt+32); TS(18);
        } __syncwarp(); }
      bar_sync(4,128);
      #pragma unroll
      for(int i=0;i<10;i++) mv[i]=ld_relaxed(p.s->mod+3*D_+tl+128*i);
    }
    if(wg>=STAG){
      #pragma unroll 1
      for(int i=(wg==1);i<(wg==2? 3:2);i+=(wg==2 && STAG==1)? 2:1) box_filter(sb+SM_KG+i*KG_WG+(wg==3? UF:0),tl);
      fence_async_smem();
      bar_sync(1+wg,128);
      mbar_arrive_pred(fb_+8*(wg-2),1,lead && wg>=2);
      TSP(79,tid==256); TSP(17,tid==384);
    } }
  if(wg<3){
    #pragma unroll 1
    for(int ch=wg; ch<5; ch+=3){
      const int it=ch>=3;
      const uint32_t U=kb+it*UF, TB=sb+tb_off(ch);
      uint32_t pp=TB+256+(16*(warp&1)+256*(warp>>1)+g-2*t-16)*4;
      uint64_t db=mkdesc(U,PLN,128,0);
      float c[32];
      if(it) mbar_wait(fb_+8,0,t0);
      uint32_t w[17];
      const uint32_t p3= warp<2? pp+4096 : TB+256+1056*4;
      if(V4) conv_load<8>(w,pp);
      #pragma unroll 1
      for(int b=0;b<2;b++){
        if(!V4) conv_load<8>(w,pp);
        conv_issue<64,8>(c,w,db,b,p.zero); wg_commit();
        pp+= b? 1536:512; db+= b? 12:4;
        if(V4) conv_load<8>(w,pp);
        wg_wait<0>(); TSP(68+b+4*it,tid==0); }
      const unsigned* gp= lane==1? p.s->cnt+32 : p.s->mod+2*D_+5*cta+ch; uint32_t gv=0;
      asm volatile("{\n.reg .pred q;\nsetp.ne.b32 q, %2, 0;\n@q ld.relaxed.gpu.global.u32 %0, [%1];\n}":"+r"(gv):"l"(gp),"r"((int)(lane<1+(warp==0))):"memory");
      #pragma unroll 1
      for(int b=0;b<2;b++){
        if(!V4) conv_load<8>(w,pp);
        conv_issue<48,8>(c,w,db,1,p.zero); wg_commit();
        pp+=512; db+=4;
        if(V4){ if(b) conv_load<3>(w,p3); else conv_load<8>(w,pp); }
        wg_wait<0>(); TSP(70+b+4*it,tid==0); }
      if(!it) mbar_wait(fb_,0,t0);
      if(!V4) conv_load<3>(w,p3);
      conv_issue<32,3>(c,w,db+8,1,p.zero);
      { const uint64_t df=mkdesc(U+UB,128,FPL,0), dt3=mkdesc(TB+4928,256,128,0);
        #pragma unroll
        for(int k=0;k<4;k++) wgmma_n32_tn(c, df+k*8*(FPL/16), dt3+k*48, 1);
        wg_commit(); }
      TSP(5+4*it,tid==0);
      uint32_t gaw=__shfl_sync(~0u,gv,0); const uint32_t xc=__shfl_sync(~0u,gv,1);
      while(__any_sync(~0u,(gaw&0xffffu)!=tag16 && (int)(clk32()-t0)>=0)) gaw=ld_relaxed(p.s->mod+2*D_+5*cta+ch);
      const float ga=bf_hi(gaw);
      wg_wait<0>(); reg_fence(c);
      TSP(6+4*it,tid==0);
      float y[16];
      { const uint32_t xa=(wg<2? sb+SM_KG+2*KG_WG+14336+wg*7168 : sb+SM_FT)+(tl&63)*16;
        if(warp<2){
          #pragma unroll
          for(int i=0;i<4;i++) sts128f(xa+i*1024,make_float4(c[4*i],c[1+4*i],c[2+4*i],c[3+4*i]));
          #pragma unroll
          for(int i=0;i<16;i++) y[i]=c[16+i];
        } else {
          #pragma unroll
          for(int i=0;i<3;i++) sts128f(xa+(4+i)*1024,make_float4(c[20+4*i],c[21+4*i],c[22+4*i],c[23+4*i]));
          #pragma unroll
          for(int i=0;i<16;i++) y[i]=c[4+i];
        }
        bar_sync(1+wg,128);
        const uint32_t ya=xa+(warp<2? 4096:0);
        #pragma unroll
        for(int i=0;i<4;i++) if(i<3 || warp>=2){ float4 h=lds128f(ya+i*1024); y[4*i]+=h.x; y[4*i+1]+=h.y; y[4*i+2]+=h.z; y[4*i+3]+=h.w; } }
      { uint32_t o[8];
        #pragma unroll
        for(int i=0;i<8;i++){ uint32_t yb=pack_bf16(y[2*i],y[2*i+1]); o[i]=pack_bf16(ga*bf_lo(yb), ga*bf_hi(yb)); }
        const uint32_t lin=((warp>>1)*32+31-(lane>>4)*8-(lane&7))*64+(2*(warp&1)+((lane>>3)&1))*16;
        const uint32_t a=TB+(lin^(((lin>>7)&7)<<4));
        stsm4t(a,o[0],o[1],o[2],o[3]); stsm4t(a-1024,o[4],o[5],o[6],o[7]);
        fence_async_smem();
        bar_sync(1+wg,128);
        if(warp==0){ if(elect_one()){ if((int)(xc-(ep+1)*128)<0) flag_wait(p.s->cnt+32,(ep+1)*128,t0);
          fence_async_global(); tma_red2(&p.x1red,0,(5*cta+ch)*32,TB); bulk_commit(); } __syncwarp(); }
      }
      TSP(7+4*it,tid==0); TSP(87,tid==256);
    }
    if(warp==0){ if(elect_one()){ bulk_wait0(); red_relaxed(p.s->cnt); } __syncwarp(); }
    TSP(8,tid==0);
  } else {
    while(true){ uint32_t bad=0;
      #pragma unroll
      for(int i=0;i<10;i++){ mv[i]^=tag16; bad|=mv[i]; }
      if(!__any_sync(~0u,bad&0xffffu)) break;
      if(__any_sync(~0u,(int)(clk32()-t0)<0)) break;
      __nanosleep(200);
      #pragma unroll
      for(int i=0;i<10;i++) mv[i]=ld_relaxed(p.s->mod+3*D_+tl+128*i);
      }
    #pragma unroll
    for(int i=0;i<5;i++){ int d=tl+128*i; sts16(MI+2560+d*2,mv[i]>>16); sts16(MI+1280+d*2,bf_bits(1.f+__uint_as_float(mv[5+i]))); }
    bar_sync(4,128);
    TSP(84,lead);
    if(wsl>=0){
      mbar_wait(w1b,0,t0);
      TSP(19,lead);
      float q0[4]={0,0,0,0}, q1[4]={0,0,0,0}, s0[4]={0,0,0,0}, s1[4]={0,0,0,0};
      const uint32_t oa=sb+SM_XS+(mi&1)*10240+(warp*20+(mi>>1))*128+(lane&7)*16;
      #pragma unroll 1
      for(int hf=0;hf<XW;hf++){ uint32_t a[40], cv[10], sv[10];
        #pragma unroll
        for(int k=0;k<5;k++){ uint32_t ad=sb+SM_WM+toff+(hf*5+k)*1024;
          ldsm4t(ad+(((mi&1)^tsw)<<4),a[8*k],a[8*k+1],a[8*k+2],a[8*k+3]); ldsm4t(ad+(((2+(mi&1))^tsw)<<4),a[8*k+4],a[8*k+5],a[8*k+6],a[8*k+7]); }
        #pragma unroll
        for(int k=0;k<10;k++){ const uint32_t va=MI+(warp*160+hf*80+k*8+2*t)*2; cv[k]=lds32(va+1280); sv[k]=lds32(va+2560); }
        #pragma unroll
        for(int k=0;k<5;k++){ uint32_t* x=a+8*k;
          mma_bf16(s0,x[0],x[1],x[2],x[3],sv[2*k],sv[2*k+1]); mma_bf16(s1,x[4],x[5],x[6],x[7],sv[2*k],sv[2*k+1]);
          uint32_t y[8];
          #pragma unroll
          for(int i=0;i<8;i++) y[i]=bf2_mul(x[i],cv[2*k+((i>>1)&1)]);
          stsm4t(oa+(hf*5+k)*256,y[0],y[1],y[2],y[3]); stsm4t(oa+20480+(hf*5+k)*256,y[4],y[5],y[6],y[7]);
          mma_bf16(q0,y[0],y[1],y[2],y[3],0x3f803f80u,0x3f803f80u); mma_bf16(q1,y[4],y[5],y[6],y[7],0x3f803f80u,0x3f803f80u); } }
      TSP(85,lead);
      if(t==0){ uint32_t a=MI+3840+warp*256+g*8; sts64f(a,q0[0],s0[0]); sts64f(a+64,q0[2],s0[2]); sts64f(a+128,q1[0],s1[0]); sts64f(a+192,q1[2],s1[2]); }
      fence_async_smem();
      bar_sync(4,128);
      if(warp==0){
        float2 a=lds64f(MI+3840+lane*8), b=lds64f(MI+3840+256+lane*8), c=lds64f(MI+3840+512+lane*8), e=lds64f(MI+3840+768+lane*8);
        const float hs=mat?0.5f:1.f;
        sts64f(MI+4864+lane*8, hs*((a.x+b.x)+(c.x+e.x)), hs*((a.y+b.y)+(c.y+e.y)));
        fence_async_smem(); __syncwarp();
        if(elect_one()){
          #pragma unroll 1
          for(int i=0;i<4;i++){ int pc=sl*4+i, s=pc/72, r=pc%72, jj= r<40? r/5 : (r-40)/4, ii= r<40? r%5 : 5+(r-40)%4; tma_st2(&p.wps,(2*ii+mat)*64,(jj*3+s)*80,sb+SM_XS+i*10240); }
          bulk_s2g(p.s->qs+mat*F_+sl*32,MI+4864,256);
          bulk_commit(); }
        __syncwarp(); }
    }
    if(warp==0){ if(elect_one()){ bulk_wait0(); red_relaxed(p.s->cnt); } __syncwarp(); }
    TSP(20,lead);
  }
  __syncthreads();
  int tile=cta;
  if(BYSM){ const int tp=cta>>1, d7=((tp-32)*37)>>8; tile=2*(tp<32? (tp&7)*8+(tp>>3) : tp<60? (tp-31-7*d7)*8+4+d7 : tp-56)+(cta&1); }
  const int m=tile>>3, j=tile&7;
  if(wg>=2){
    asm volatile("setmaxnreg.dec.sync.aligned.u32 48;");
    if(wid==8){ if(elect_one()){
      const unsigned char* wp=(const unsigned char*)p.s->Wp + (size_t)j*30*18432;
      TS(21);
      flag_wait(p.s->cnt,(ep+1)*512,t0); fence_async_global();
      TS(22);
      int s=0, ph=1; int kc=0;
      #pragma unroll 1
      for(int i=0;i<30;i++){
        mbar_wait(emptyb+8*s,ph,t0);
        uint32_t st=sb+s*STG, fb=fullb+8*s;
        mbar_expect_tx(fb,STG);
        tma_ld2(st,&p.x1a,m*128,kc*64,fb);
        tma_ld2(st+8192,&p.x1a,m*128+64,kc*64,fb);
        bulk_g2s(st+16384,wp,18432,fb);
        wp+=18432; if(++kc==10) kc=0;
        if(++s==NSTG){s=0;ph^=1;}
      }
      const unsigned char* gp=(const unsigned char*)p.s->G+(size_t)m*27*16384; const unsigned char* w2=(const unsigned char*)p.s->W2p+(size_t)j*27*10240;
      uint32_t dep=emptyb+48; s=0; ph=0;
      #pragma unroll 1
      for(int i=0;i<27;i++){
        if(kc==0||kc==5){ mbar_wait(dep,0,t0); dep+= dep==emptyb+56? 16:8; fence_async_global(); }
        if(++kc==9) kc=0;
        if(i<NST2) mbar_wait(emptyb+8*(i-(i>3)),0,t0);
        else mbar_wait(empty2+8*s,ph,t0);
        uint32_t st=sb+s*STG2, fb=full2+8*s;
        mbar_expect_tx(fb,STG2);
        bulk_g2s(st+16384,w2,10240,fb);
        bulk_g2s(st,gp,16384,fb);
        if(i==RESAT){ mbar_expect_tx(resb,20480); tma_ld2(sb+SM_RES,&p.x1r,m*128,j*80,resb); tma_ld2(sb+SM_RES+10240,&p.x1r,m*128+64,j*80,resb); }
        gp+=16384; w2+=10240;
        if(++s==NST2){s=0; ph^=(i>=NST2);}
      }
    } }
    else if(wid==9){
      #pragma unroll 1
      for(int pt=0;pt<6;pt++){
        bar_sync((pt&1)? 5:11,160);
        if(elect_one()){
          const int kb0=(pt>>1)*72+((pt&1)? 40+j*4 : j*5);
          bulk_s2g((unsigned char*)p.s->G+(size_t)(m*216+kb0)*2048,sb+SM_GS+(pt&1)*10240,(5-(pt&1))*2048);
          bulk_commit(); bulk_wait0_read(); mbar_arrive_pred(gsb,1,pt&1);
          bulk_wait0(); red_relaxed(p.s->gflag+m*32+pt); TS(62+pt);
        }
        __syncwarp();
      }
    }
    else if(wid==10){
      while(__any_sync(~0u,(int)(ld_relaxed(p.s->cnt+64)-(ep+1)*4)<0 && (int)(clk32()-t0)>=0)) __nanosleep(200);
      TSP(81,lane==0);
      const unsigned* gf=p.s->gflag+m*32+min(lane,5); const unsigned tgt=(ep+1)*8;
      int done=0; unsigned v[PDEPTH];
      #pragma unroll
      for(int k=0;k<PDEPTH;k++){ v[k]=ld_relaxed(gf); if(PDEPTH>1) __nanosleep(POLLNS); }
      while(done<6){
        #pragma unroll
        for(int k=0;k<PDEPTH;k++){
          const unsigned ok=__ballot_sync(~0u,(int)(v[k]-tgt)>=0 || (int)(clk32()-t0)<0);
          v[k]=ld_relaxed(gf);
          const int nd=__ffs(~ok|64)-1;
          mbar_arrive_pred(emptyb+48+8*lane+(lane>1? 8:0),1,lane>=done && lane<nd); TSP(23+lane,lane>=done && lane<nd);
          done=max(done,nd); } }
    }
    else if(wid==11){
      const unsigned* gbp=p.s->mod+5*D_+j*80; uint32_t a,b,c;
      while(true){ a=ld_relaxed(gbp+lane)^tag16; b=ld_relaxed(gbp+32+lane)^tag16; c=ld_relaxed(gbp+64+(lane&15))^tag16;
        if(!__any_sync(~0u,((a|b|c)&0xffffu) && (int)(clk32()-t0)>=0)) break;
        __nanosleep(200); }
      mbar_wait(gsb,0,t0);
      sts16(sb+SM_QS+lane*2,a>>16); sts16(sb+SM_QS+64+lane*2,b>>16); if(lane<16) sts16(sb+SM_QS+128+lane*2,c>>16);
      bar_arrive(12,160);
    }
    else if(wg==3){
      const unsigned tag=ep+1;
      float su0=0,su1=0,sq0=0,sq1=0; float2 qa[2], qb[2];
      { const int row=warp*16+(lane>>4)*8+(lane&7);
        const uint32_t off=(j>>2)*8192+row*128+((((j&3)*2+((lane>>3)&1))^(lane&7))<<4);
        int s=0, ph=0;
        #pragma unroll 1
        for(int i=0;i<10;i++){
          mbar_wait(fullb+8*s,ph,t0);
          uint32_t a0,a1,a2,a3; ldsm4t(sb+s*STG+off,a0,a1,a2,a3);
          if(i==0){
            #pragma unroll
            for(int k=0;k<2;k++){ int q=min(tl+128*k,215); int r=q%72, f=(q/72)*576+(r<40? j*40+r : 280+j*32+r); qa[k]=__ldcg(p.s->qs+f); qb[k]=__ldcg(p.s->qs+F_+f); } }
          float x0=bf_lo(a0),x1=bf_hi(a0),x2=bf_lo(a2),x3=bf_hi(a2), y0=bf_lo(a1),y1=bf_hi(a1),y2=bf_lo(a3),y3=bf_hi(a3);
          __syncwarp();
          mbar_arrive_pred(emptyb+8*s,1,lane==0);
          su0+=(x0+x1)+(x2+x3); su1+=(y0+y1)+(y2+y3);
          sq0=fmaf(x0,x0,fmaf(x1,x1,fmaf(x2,x2,fmaf(x3,x3,sq0)))); sq1=fmaf(y0,y0,fmaf(y1,y1,fmaf(y2,y2,fmaf(y3,y3,sq1))));
          if(++s==NSTG){s=0;ph^=1;} } }
      { float a=(t&1)?sq0:su0, b=(t&1)?su0:sq0, c=(t&1)?sq1:su1, e=(t&1)?su1:sq1;
        a+=__shfl_xor_sync(~0u,b,1); c+=__shfl_xor_sync(~0u,e,1);
        float k=(t&2)?c:a, o=(t&2)?a:c; k+=__shfl_xor_sync(~0u,o,2);
        asm volatile("st.relaxed.gpu.global.b64 [%0], %1;"::"l"((unsigned long long*)(p.s->st2+warp*L_+m*128+j*16+(t>>1)*8+g)+(t&1)),
          "l"(((unsigned long long)tag<<32)|__float_as_uint(k)):"memory"); }
      TSP(80,lead);
      #pragma unroll
      for(int k=0;k<2;k++){ int q=tl+128*k; if(q<216) sts128f(sb+SM_QS+q*16,make_float4(qa[k].x,qa[k].y,qb[k].x,qb[k].y)); }
      { unsigned long long a[4],b[4];
        while(true){ unsigned bad=0;
          __nanosleep(STNS);
          #pragma unroll
          for(int w=0;w<4;w++) asm volatile("ld.relaxed.gpu.global.v2.b64 {%0,%1}, [%2];":"=l"(a[w]),"=l"(b[w]):"l"(p.s->st2+w*L_+m*128+tl):"memory");
          #pragma unroll
          for(int w=0;w<4;w++) bad|=((unsigned)(a[w]>>32)^tag)|((unsigned)(b[w]>>32)^tag);
          if(!__any_sync(~0u,bad && (int)(clk32()-t0)>=0)) break; }
        const float su=(__uint_as_float((unsigned)a[0])+__uint_as_float((unsigned)a[1]))+(__uint_as_float((unsigned)a[2])+__uint_as_float((unsigned)a[3]));
        const float sq=(__uint_as_float((unsigned)b[0])+__uint_as_float((unsigned)b[1]))+(__uint_as_float((unsigned)b[2])+__uint_as_float((unsigned)b[3]));
        const float mu=su*(1.f/D_), rs=rsqrtf(fmaxf(sq*(1.f/D_)-mu*mu,0.f)+1e-5f);
        sts64f(sb+SM_ST+tl*8, rs, -rs*mu); }
      bar_arrive(6,256); bar_arrive(7,256);
      TSP(29,lead);
    }
  } else {
    asm volatile("setmaxnreg.inc.sync.aligned.u32 208;");
    const uint32_t roff=(lane>>4)*1024+(lane&7)*128+(((2*warp+((lane>>3)&1))^(lane&7))<<4);
    #pragma unroll 1
    for(int sub=wg; sub<3; sub+=2){
      float acc0[72], acc1[72];
      int i0=sub*10; int s=i0%NSTG, ph=(i0/NSTG)&1, ps=0;
      const uint32_t rel= sub? 5:1;
      if(sub>0) bar_sync(7+sub,256);
      #pragma unroll 1
      for(int i=0;i<10;i++){
        mbar_wait(fullb+8*s,ph,t0);
        bar_arrive_pred(8+sub, 256, i==9);
        TSP(30+i0+i,lead);
        uint32_t st=sb+s*STG;
        uint64_t da=mkdesc(st,16,1024,1), db=mkdesc(st+16384,2304,128,0);
        wg_fence();
        #pragma unroll
        for(int kk=0;kk<4;kk++){
          wgmma_n144_tt(acc0, da+kk*128, db+kk*288, (i|kk)!=0);
          wgmma_n144_tt(acc1, da+512+kk*128, db+kk*288, (i|kk)!=0);
          if(kk==REL1){ wg_commit(); wg_wait<1>(); mbar_arrive_pred(emptyb+8*ps,rel,lead && i>0); }
        }
        if(REL1<3) wg_commit();
        ps=s; if(++s==NSTG){s=0;ph^=1;}
      }
      wg_wait<0>();
      reg_fence(acc0); reg_fence(acc1);
      mbar_arrive_pred(emptyb+8*ps,rel,lead);
      TSP(88+sub,lead);
      if(sub<2) bar_sync(6+sub,256);
      if(sub) mbar_wait(gsb,(sub-1)&1,t0);
      if(EPI==EPI2 || sub<2) geglu<EPI>(acc0,acc1,sb,sub,warp,lane,p.zero); else geglu<EPI2>(acc0,acc1,sb,sub,warp,lane,p.zero);
      fence_async_smem();
      bar_arrive(5,160);
      TSP(91+sub,lead);
    }
    if(wg==1){
      float acc0[40], acc1[40]; uint32_t res[40], gbw[10];
      int s=0, ph=0, ps=0;
      bar_sync(12,160);
      #pragma unroll
      for(int i=0;i<10;i++) gbw[i]=lds32(sb+SM_QS+i*16+t*4);
      bar_sync(10,256);
      #pragma unroll 1
      for(int i=0;i<27;i++){
        mbar_wait(full2+8*s,ph,t0);
        TSP(100+i,lead && i<26);
        uint32_t st=sb+s*STG2;
        uint64_t da=mkdesc(st,2048,128,0), db=mkdesc(st+16384,1280,128,0);
        wg_fence();
        #pragma unroll
        for(int kk=0;kk<4;kk++){
          wgmma_n80_nt(acc0, da+kk*256, db+kk*160, (i|kk)!=0);
          wgmma_n80_nt(acc1, da+64+kk*256, db+kk*160, (i|kk)!=0);
          if(kk==REL2){ wg_commit(); wg_wait<1>(); mbar_arrive_pred(empty2+8*ps,1,lead && i>0); }
        }
        if(REL2<3) wg_commit();
        ps=s; if(++s==NST2){s=0;ph^=1;}
      }
      mbar_wait(resb,0,t0);
      #pragma unroll
      for(int k=0;k<10;k++) ldsm4t(sb+SM_RES+roff+(k/5)*10240+(k%5)*2048,res[4*k],res[4*k+1],res[4*k+2],res[4*k+3]);
      const uint32_t ob=sb+s*STG2+warp*2560;
      const uint32_t oa=ob+(lane&15)*160+(lane>>4)*16;
      wg_wait<0>();
      reg_fence(acc0); reg_fence(acc1);
      TSP(94,lead);
      #pragma unroll
      for(int h=0;h<2;h++){
        #pragma unroll
        for(int k=0;k<5;k++){ uint32_t o[4];
          #pragma unroll
          for(int r=0;r<4;r++){ const int a=8*k+2*r; o[r]=bf2_fma(h? pack_bf16(acc1[a],acc1[a+1]) : pack_bf16(acc0[a],acc0[a+1]), gbw[2*k+(r>>1)], res[20*h+4*k+r]); }
          stsm4(oa+h*10240+k*32,o[0],o[1],o[2],o[3]); }
        fence_async_smem();
        __syncwarp();
        if(elect_one()){ tma_st2(&p.out, j*80, m*128+h*64+warp*16, ob+h*10240); bulk_commit(); if(h) bulk_wait0_read(); }
        __syncwarp();
      }
      TSP(95,lead);
    }
  }
}

typedef CUresult (*EncFn)(CUtensorMap*, CUtensorMapDataType, cuuint32_t, void*, const cuuint64_t*, const cuuint64_t*, const cuuint32_t*, const cuuint32_t*, CUtensorMapInterleave, CUtensorMapSwizzle, CUtensorMapL2promotion, CUtensorMapFloatOOBfill);
static void mk2(EncFn enc, CUtensorMap* m, const void* p, cuuint64_t d0, cuuint64_t d1, cuuint64_t s1, cuuint32_t b0, cuuint32_t b1, CUtensorMapSwizzle sw, CUtensorMapL2promotion pr=CU_TENSOR_MAP_L2_PROMOTION_NONE){
  cuuint64_t gd[2]={d0,d1}, gs[1]={s1}; cuuint32_t bx[2]={b0,b1}, es[2]={1,1};
  CUresult r=enc(m,CU_TENSOR_MAP_DATA_TYPE_BFLOAT16,2,(void*)p,gd,gs,bx,es,CU_TENSOR_MAP_INTERLEAVE_NONE,sw,pr,CU_TENSOR_MAP_FLOAT_OOB_FILL_NONE);
  (void)r;
}
extern "C" void kernel_launch(void* const* d_in, const int* in_sizes, int n_in, void* d_out, int out_size){
  Params p;
  p.x=(const bf16*)d_in[0]; for(int i=0;i<6;i++) p.in[i]=(const bf16*)d_in[1+i];
  p.in[6]=p.in[7]=(const bf16*)d_in[11]; p.wgp=(const bf16*)d_in[8]; p.wup=(const bf16*)d_in[9]; p.wdp=(const bf16*)d_in[10];
  const bf16* wm=(const bf16*)d_in[12]; p.zero=0;
  EncFn enc=nullptr; cudaDriverEntryPointQueryResult qr;
  cudaGetDriverEntryPoint("cuTensorMapEncodeTiled",(void**)&enc,cudaEnableDefault,&qr);
  cudaGetSymbolAddress((void**)&p.s,g_scr); void *px1=p.s->x1T,*pin=p.s->inbox,*pwp=p.s->Wp;
  mk2(enc,&p.x1a,px1,L_,D_,L_*2,64,64,CU_TENSOR_MAP_SWIZZLE_128B);
  mk2(enc,&p.x1r,px1,L_,D_,L_*2,64,80,CU_TENSOR_MAP_SWIZZLE_128B);
  mk2(enc,&p.out,d_out,D_,L_,D_*2,80,16,CU_TENSOR_MAP_SWIZZLE_NONE);
  mk2(enc,&p.xts,px1,L_,D_,L_*2,16,160,CU_TENSOR_MAP_SWIZZLE_32B);
  mk2(enc,&p.xns,pin,128*80,128,128*160,80,128,CU_TENSOR_MAP_SWIZZLE_NONE);
  mk2(enc,&p.x1red,px1,64,D_*32,128,64,32,CU_TENSOR_MAP_SWIZZLE_128B);
  mk2(enc,&p.wm,wm,6*D_,D_,6*D_*2,32,160,CU_TENSOR_MAP_SWIZZLE_64B,PROMO);
  mk2(enc,&p.wg,p.wgp,F_,D_,F_*2,32,160,CU_TENSOR_MAP_SWIZZLE_64B,PROMO);
  mk2(enc,&p.wu,p.wup,F_,D_,F_*2,32,160,CU_TENSOR_MAP_SWIZZLE_64B,PROMO);
  mk2(enc,&p.wps,pwp,1152,24*80,2304,64,80,CU_TENSOR_MAP_SWIZZLE_NONE);
  int dev=0, nsm=0; cudaGetDevice(&dev); cudaDeviceGetAttribute(&nsm,cudaDevAttrMultiProcessorCount,dev);
  if(nsm==132){ cudaFuncSetAttribute(fused_kernel<true>,cudaFuncAttributeMaxDynamicSharedMemorySize,SM_ALLOC); fused_kernel<true><<<132,512,SM_ALLOC>>>(p); }
  else { cudaFuncSetAttribute(fused_kernel<false>,cudaFuncAttributeMaxDynamicSharedMemorySize,SM_ALLOC); fused_kernel<false><<<132,512,SM_ALLOC>>>(p); }
}
```

```cpp
#include <cuda_runtime.h>
#include <cuda_bf16.h>
#include <cuda_fp16.h>
#include <cuda.h>
#include <stdint.h>

typedef __nv_bfloat16 bf16;
constexpr int L_ = 2048, D_ = 640, N_ = 128, F_ = 1728;

__device__ __forceinline__ uint32_t smem_u32(const void* p){ return (uint32_t)__cvta_generic_to_shared(p); }
__device__ __forceinline__ uint32_t opaque(uint32_t x){ uint32_t y; asm volatile("mov.u32 %0, %1;":"=r"(y):"r"(x)); return y; }
__device__ __forceinline__ uint32_t clk32(){ uint32_t c; asm volatile("mov.u32 %0, %%clock;":"=r"(c)); return c; }
__device__ __forceinline__ bool elect_one(){ uint32_t p; asm volatile("{\n.reg .pred P;\nelect.sync _|P, 0xffffffff;\nselp.u32 %0,1,0,P;\n}":"=r"(p)); return p; }
__device__ __forceinline__ void mbar_init(uint32_t bar, uint32_t cnt){ asm volatile("mbarrier.init.shared::cta.b64 [%0], %1;"::"r"(bar),"r"(cnt):"memory"); }
__device__ __forceinline__ void mbar_expect_tx(uint32_t bar, uint32_t bytes){ asm volatile("mbarrier.arrive.expect_tx.shared::cta.b64 _, [%0], %1;"::"r"(bar),"r"(bytes):"memory"); }
__device__ __forceinline__ void mbar_arrive_pred(uint32_t bar, uint32_t cnt, int pred){
  asm volatile("{\n.reg .pred p;\nsetp.ne.b32 p, %2, 0;\n@p mbarrier.arrive.shared::cta.b64 _, [%0], %1;\n}"::"r"(bar),"r"(cnt),"r"(pred):"memory"); }
__device__ __forceinline__ void mbar_wait(uint32_t bar, uint32_t parity, uint32_t){
  asm volatile("{\n.reg .pred p;\n.reg .b32 c;\nmbarrier.try_wait.parity.shared::cta.b64 p, [%0], %1;\n@p bra LD;\nmov.u32 c, 0;\n"
               "LW:\nmbarrier.try_wait.parity.shared::cta.b64 p, [%0], %1;\n@p bra LD;\nadd.u32 c, c, 1;\nsetp.lt.u32 p, c, 262144;\n@p bra LW;\nLD:\n}"::"r"(bar),"r"(parity):"memory"); }
__device__ __forceinline__ void flag_wait(const unsigned* f, unsigned target, uint32_t t0){
  asm volatile("{\n.reg .pred p;\n.reg .b32 c;\nLW:\nld.acquire.gpu.global.u32 c, [%0];\nsub.u32 c, c, %1;\nsetp.ge.s32 p, c, 0;\n@p bra LD;\n"
               "mov.u32 c, %%clock;\nsub.u32 c, c, %2;\nsetp.lt.s32 p, c, 0;\n@p bra LD;\nbra LW;\nLD:\n}"::"l"(f),"r"(target),"r"(t0):"memory"); }
__device__ __forceinline__ void red_release(unsigned* f, unsigned v){ asm volatile("red.release.gpu.global.add.u32 [%0], %1;"::"l"(f),"r"(v):"memory"); }
__device__ __forceinline__ unsigned ld_relaxed(const unsigned* f){ unsigned v; asm volatile("ld.relaxed.gpu.global.u32 %0, [%1];":"=r"(v):"l"(f):"memory"); return v; }
__device__ __forceinline__ void fence_async_smem(){ asm volatile("fence.proxy.async.shared::cta;":::"memory"); }
__device__ __forceinline__ void fence_async_all(){ asm volatile("fence.proxy.async;":::"memory"); }
__device__ __forceinline__ void bar_sync(int id, int n){ asm volatile("bar.sync %0, %1;"::"r"(id),"r"(n):"memory"); }
__device__ __forceinline__ void bar_arrive(int id, int n){ asm volatile("bar.arrive %0, %1;"::"r"(id),"r"(n):"memory"); }
__device__ __forceinline__ void bulk_g2s(uint32_t dst, const void* src, uint32_t bytes, uint32_t bar){
  asm volatile("cp.async.bulk.shared::cluster.global.mbarrier::complete_tx::bytes [%0], [%1], %2, [%3];"::"r"(dst),"l"(src),"r"(bytes),"r"(bar):"memory"); }
__device__ __forceinline__ void tma_ld2(uint32_t dst, const CUtensorMap* m, int c0, int c1, uint32_t bar){
  asm volatile("cp.async.bulk.tensor.2d.shared::cluster.global.mbarrier::complete_tx::bytes [%0], [%1, {%3, %4}], [%2];"::"r"(dst),"l"(m),"r"(bar),"r"(c0),"r"(c1):"memory"); }
__device__ __forceinline__ void tma_ld3(uint32_t dst, const CUtensorMap* m, int c0, int c1, int c2, uint32_t bar){
  asm volatile("cp.async.bulk.tensor.3d.shared::cluster.global.mbarrier::complete_tx::bytes [%0], [%1, {%3, %4, %5}], [%2];"::"r"(dst),"l"(m),"r"(bar),"r"(c0),"r"(c1),"r"(c2):"memory"); }
__device__ __forceinline__ void tma_st2(const CUtensorMap* m, int c0, int c1, uint32_t src){
  asm volatile("cp.async.bulk.tensor.2d.global.shared::cta.bulk_group [%0, {%2, %3}], [%1];"::"l"(m),"r"(src),"r"(c0),"r"(c1):"memory"); }
__device__ __forceinline__ void bulk_commit(){ asm volatile("cp.async.bulk.commit_group;":::"memory"); }
__device__ __forceinline__ void bulk_wait0(){ asm volatile("cp.async.bulk.wait_group 0;":::"memory"); }
__device__ __forceinline__ void bulk_wait0_read(){ asm volatile("cp.async.bulk.wait_group.read 0;":::"memory"); }
__device__ __forceinline__ void prefetch_tmap(const CUtensorMap* m){ asm volatile("prefetch.tensormap [%0];"::"l"(m):"memory"); }
__device__ __forceinline__ void wg_fence(){ asm volatile("wgmma.fence.sync.aligned;":::"memory"); }
__device__ __forceinline__ void wg_commit(){ asm volatile("wgmma.commit_group.sync.aligned;":::"memory"); }
template<int N> __device__ __forceinline__ void wg_wait(){ asm volatile("wgmma.wait_group.sync.aligned %0;"::"n"(N):"memory"); }
template<int N> __device__ __forceinline__ void reg_fence(float (&d)[N]){
  #pragma unroll
  for(int i=0;i<N;i++) asm volatile("":"+f"(d[i])::"memory"); }
__device__ __forceinline__ uint64_t mkdesc(uint32_t addr, uint32_t lbo, uint32_t sbo, uint32_t swz){
  return (uint64_t)((addr&0x3FFFF)>>4) | ((uint64_t)(lbo>>4)<<16) | ((uint64_t)(sbo>>4)<<32) | ((uint64_t)swz<<62); }
__device__ __forceinline__ void stsm4(uint32_t a, uint32_t r0, uint32_t r1, uint32_t r2, uint32_t r3){
  asm volatile("stmatrix.sync.aligned.m8n8.x4.shared.b16 [%0], {%1,%2,%3,%4};"::"r"(a),"r"(r0),"r"(r1),"r"(r2),"r"(r3):"memory"); }
__device__ __forceinline__ void stsm4t(uint32_t a, uint32_t r0, uint32_t r1, uint32_t r2, uint32_t r3){
  asm volatile("stmatrix.sync.aligned.m8n8.x4.trans.shared.b16 [%0], {%1,%2,%3,%4};"::"r"(a),"r"(r0),"r"(r1),"r"(r2),"r"(r3):"memory"); }
__device__ __forceinline__ void ldsm4t(uint32_t a, uint32_t& r0, uint32_t& r1, uint32_t& r2, uint32_t& r3){
  asm volatile("ldmatrix.sync.aligned.m8n8.x4.trans.shared.b16 {%0,%1,%2,%3}, [%4];":"=r"(r0),"=r"(r1),"=r"(r2),"=r"(r3):"r"(a):"memory"); }
__device__ __forceinline__ uint4 lds128(uint32_t a){ uint4 v; asm volatile("ld.shared.v4.u32 {%0,%1,%2,%3}, [%4];":"=r"(v.x),"=r"(v.y),"=r"(v.z),"=r"(v.w):"r"(a):"memory"); return v; }
__device__ __forceinline__ float4 lds128f(uint32_t a){ float4 v; asm volatile("ld.shared.v4.f32 {%0,%1,%2,%3}, [%4];":"=f"(v.x),"=f"(v.y),"=f"(v.z),"=f"(v.w):"r"(a):"memory"); return v; }
__device__ __forceinline__ float2 lds64f(uint32_t a){ float2 v; asm volatile("ld.shared.v2.f32 {%0,%1}, [%2];":"=f"(v.x),"=f"(v.y):"r"(a):"memory"); return v; }
__device__ __forceinline__ void sts64f(uint32_t a, float x, float y){ asm volatile("st.shared.v2.f32 [%0], {%1,%2};"::"r"(a),"f"(x),"f"(y):"memory"); }
__device__ __forceinline__ void sts128f(uint32_t a, float4 v){ asm volatile("st.shared.v4.f32 [%0], {%1,%2,%3,%4};"::"r"(a),"f"(v.x),"f"(v.y),"f"(v.z),"f"(v.w):"memory"); }
__device__ __forceinline__ uint32_t pack_bf16(float lo, float hi){ uint32_t r; asm("cvt.rn.bf16x2.f32 %0, %1, %2;":"=r"(r):"f"(hi),"f"(lo)); return r; }
__device__ __forceinline__ float bf_lo(uint32_t v){ return __uint_as_float(v<<16); }
__device__ __forceinline__ float bf_hi(uint32_t v){ return __uint_as_float(v&0xffff0000u); }
__device__ __forceinline__ float tanh_fast(float x){ float y; asm("tanh.approx.f32 %0, %1;":"=f"(y):"f"(x)); return y; }
__device__ __forceinline__ float bfr(float x){ return __uint_as_float(pack_bf16(0.f,x)); }

__device__ __forceinline__ void wgmma_n144_tt(float (&d)[72], uint64_t da, uint64_t db, int sc){
  asm volatile("{\n.reg .pred p;\nsetp.ne.b32 p, %74, 0;\nwgmma.mma_async.sync.aligned.m64n144k16.f32.bf16.bf16 {%0,%1,%2,%3,%4,%5,%6,%7,%8,%9,%10,%11,%12,%13,%14,%15,%16,%17,%18,%19,%20,%21,%22,%23,%24,%25,%26,%27,%28,%29,%30,%31,%32,%33,%34,%35,%36,%37,%38,%39,%40,%41,%42,%43,%44,%45,%46,%47,%48,%49,%50,%51,%52,%53,%54,%55,%56,%57,%58,%59,%60,%61,%62,%63,%64,%65,%66,%67,%68,%69,%70,%71}, %72, %73, p, 1, 1, 1, 1;\n}\n"
   : "+f"(d[0]),"+f"(d[1]),"+f"(d[2]),"+f"(d[3]),"+f"(d[4]),"+f"(d[5]),"+f"(d[6]),"+f"(d[7]),"+f"(d[8]),"+f"(d[9]),"+f"(d[10]),"+f"(d[11]),"+f"(d[12]),"+f"(d[13]),"+f"(d[14]),"+f"(d[15]),"+f"(d[16]),"+f"(d[17]),"+f"(d[18]),"+f"(d[19]),"+f"(d[20]),"+f"(d[21]),"+f"(d[22]),"+f"(d[23]),"+f"(d[24]),"+f"(d[25]),"+f"(d[26]),"+f"(d[27]),"+f"(d[28]),"+f"(d[29]),"+f"(d[30]),"+f"(d[31]),"+f"(d[32]),"+f"(d[33]),"+f"(d[34]),"+f"(d[35]),"+f"(d[36]),"+f"(d[37]),"+f"(d[38]),"+f"(d[39]),"+f"(d[40]),"+f"(d[41]),"+f"(d[42]),"+f"(d[43]),"+f"(d[44]),"+f"(d[45]),"+f"(d[46]),"+f"(d[47]),"+f"(d[48]),"+f"(d[49]),"+f"(d[50]),"+f"(d[51]),"+f"(d[52]),"+f"(d[53]),"+f"(d[54]),"+f"(d[55]),"+f"(d[56]),"+f"(d[57]),"+f"(d[58]),"+f"(d[59]),"+f"(d[60]),"+f"(d[61]),"+f"(d[62]),"+f"(d[63]),"+f"(d[64]),"+f"(d[65]),"+f"(d[66]),"+f"(d[67]),"+f"(d[68]),"+f"(d[69]),"+f"(d[70]),"+f"(d[71])
   : "l"(da), "l"(db), "r"(sc));
}

__device__ __forceinline__ void wgmma_n80_nt(float (&d)[40], uint64_t da, uint64_t db, int sc){
  asm volatile("{\n.reg .pred p;\nsetp.ne.b32 p, %42, 0;\nwgmma.mma_async.sync.aligned.m64n80k16.f32.bf16.bf16 {%0,%1,%2,%3,%4,%5,%6,%7,%8,%9,%10,%11,%12,%13,%14,%15,%16,%17,%18,%19,%20,%21,%22,%23,%24,%25,%26,%27,%28,%29,%30,%31,%32,%33,%34,%35,%36,%37,%38,%39}, %40, %41, p, 1, 1, 0, 1;\n}\n"
   : "+f"(d[0]),"+f"(d[1]),"+f"(d[2]),"+f"(d[3]),"+f"(d[4]),"+f"(d[5]),"+f"(d[6]),"+f"(d[7]),"+f"(d[8]),"+f"(d[9]),"+f"(d[10]),"+f"(d[11]),"+f"(d[12]),"+f"(d[13]),"+f"(d[14]),"+f"(d[15]),"+f"(d[16]),"+f"(d[17]),"+f"(d[18]),"+f"(d[19]),"+f"(d[20]),"+f"(d[21]),"+f"(d[22]),"+f"(d[23]),"+f"(d[24]),"+f"(d[25]),"+f"(d[26]),"+f"(d[27]),"+f"(d[28]),"+f"(d[29]),"+f"(d[30]),"+f"(d[31]),"+f"(d[32]),"+f"(d[33]),"+f"(d[34]),"+f"(d[35]),"+f"(d[36]),"+f"(d[37]),"+f"(d[38]),"+f"(d[39])
   : "l"(da), "l"(db), "r"(sc));
}

__device__ __forceinline__ void wgmma_n64_rs(float (&d)[32], uint32_t a0, uint32_t a1, uint32_t a2, uint32_t a3, uint64_t db, int sc){
  asm volatile("{\n.reg .pred p;\nsetp.ne.b32 p, %37, 0;\nwgmma.mma_async.sync.aligned.m64n64k16.f32.bf16.bf16 {%0,%1,%2,%3,%4,%5,%6,%7,%8,%9,%10,%11,%12,%13,%14,%15,%16,%17,%18,%19,%20,%21,%22,%23,%24,%25,%26,%27,%28,%29,%30,%31}, {%32,%33,%34,%35}, %36, p, 1, 1, 0;\n}\n"
   : "+f"(d[0]),"+f"(d[1]),"+f"(d[2]),"+f"(d[3]),"+f"(d[4]),"+f"(d[5]),"+f"(d[6]),"+f"(d[7]),"+f"(d[8]),"+f"(d[9]),"+f"(d[10]),"+f"(d[11]),"+f"(d[12]),"+f"(d[13]),"+f"(d[14]),"+f"(d[15]),"+f"(d[16]),"+f"(d[17]),"+f"(d[18]),"+f"(d[19]),"+f"(d[20]),"+f"(d[21]),"+f"(d[22]),"+f"(d[23]),"+f"(d[24]),"+f"(d[25]),"+f"(d[26]),"+f"(d[27]),"+f"(d[28]),"+f"(d[29]),"+f"(d[30]),"+f"(d[31])
   : "r"(a0),"r"(a1),"r"(a2),"r"(a3), "l"(db), "r"(sc));
}

__device__ __forceinline__ void wgmma_n48_rs(float (&d)[32], uint32_t a0, uint32_t a1, uint32_t a2, uint32_t a3, uint64_t db, int sc){
  asm volatile("{\n.reg .pred p;\nsetp.ne.b32 p, %29, 0;\nwgmma.mma_async.sync.aligned.m64n48k16.f32.bf16.bf16 {%0,%1,%2,%3,%4,%5,%6,%7,%8,%9,%10,%11,%12,%13,%14,%15,%16,%17,%18,%19,%20,%21,%22,%23}, {%24,%25,%26,%27}, %28, p, 1, 1, 0;\n}\n"
   : "+f"(d[0]),"+f"(d[1]),"+f"(d[2]),"+f"(d[3]),"+f"(d[4]),"+f"(d[5]),"+f"(d[6]),"+f"(d[7]),"+f"(d[8]),"+f"(d[9]),"+f"(d[10]),"+f"(d[11]),"+f"(d[12]),"+f"(d[13]),"+f"(d[14]),"+f"(d[15]),"+f"(d[16]),"+f"(d[17]),"+f"(d[18]),"+f"(d[19]),"+f"(d[20]),"+f"(d[21]),"+f"(d[22]),"+f"(d[23])
   : "r"(a0),"r"(a1),"r"(a2),"r"(a3), "l"(db), "r"(sc));
}

__device__ __forceinline__ void wgmma_n32_rs(float (&d)[32], uint32_t a0, uint32_t a1, uint32_t a2, uint32_t a3, uint64_t db, int sc){
  asm volatile("{\n.reg .pred p;\nsetp.ne.b32 p, %21, 0;\nwgmma.mma_async.sync.aligned.m64n32k16.f32.bf16.bf16 {%0,%1,%2,%3,%4,%5,%6,%7,%8,%9,%10,%11,%12,%13,%14,%15}, {%16,%17,%18,%19}, %20, p, 1, 1, 0;\n}\n"
   : "+f"(d[0]),"+f"(d[1]),"+f"(d[2]),"+f"(d[3]),"+f"(d[4]),"+f"(d[5]),"+f"(d[6]),"+f"(d[7]),"+f"(d[8]),"+f"(d[9]),"+f"(d[10]),"+f"(d[11]),"+f"(d[12]),"+f"(d[13]),"+f"(d[14]),"+f"(d[15])
   : "r"(a0),"r"(a1),"r"(a2),"r"(a3), "l"(db), "r"(sc));
}

__device__ __forceinline__ void wgmma_n32_tn(float (&d)[32], uint64_t da, uint64_t db, int sc){
  asm volatile("{\n.reg .pred p;\nsetp.ne.b32 p, %18, 0;\nwgmma.mma_async.sync.aligned.m64n32k16.f32.bf16.bf16 {%0,%1,%2,%3,%4,%5,%6,%7,%8,%9,%10,%11,%12,%13,%14,%15}, %16, %17, p, 1, 1, 1, 0;\n}\n"
   : "+f"(d[0]),"+f"(d[1]),"+f"(d[2]),"+f"(d[3]),"+f"(d[4]),"+f"(d[5]),"+f"(d[6]),"+f"(d[7]),"+f"(d[8]),"+f"(d[9]),"+f"(d[10]),"+f"(d[11]),"+f"(d[12]),"+f"(d[13]),"+f"(d[14]),"+f"(d[15])
   : "l"(da), "l"(db), "r"(sc));
}

__device__ __forceinline__ void wgmma_n16_f16(float (&d)[8], uint64_t da, uint64_t db, int sc){
  asm volatile("{\n.reg .pred p;\nsetp.ne.b32 p, %10, 0;\nwgmma.mma_async.sync.aligned.m64n16k16.f32.f16.f16 {%0,%1,%2,%3,%4,%5,%6,%7}, %8, %9, p, 1, 1, 1, 1;\n}\n"
   : "+f"(d[0]),"+f"(d[1]),"+f"(d[2]),"+f"(d[3]),"+f"(d[4]),"+f"(d[5]),"+f"(d[6]),"+f"(d[7])
   : "l"(da), "l"(db), "r"(sc));
}

__device__ __forceinline__ void wgmma_n8_rs(float (&d)[4], uint32_t a0, uint32_t a1, uint32_t a2, uint32_t a3, uint64_t db, int sc){
  asm volatile("{\n.reg .pred p;\nsetp.ne.b32 p, %9, 0;\nwgmma.mma_async.sync.aligned.m64n8k16.f32.bf16.bf16 {%0,%1,%2,%3}, {%4,%5,%6,%7}, %8, p, 1, 1, 0;\n}\n"
   : "+f"(d[0]),"+f"(d[1]),"+f"(d[2]),"+f"(d[3])
   : "r"(a0),"r"(a1),"r"(a2),"r"(a3), "l"(db), "r"(sc));
}

__device__ __forceinline__ void ldsm4(uint32_t a, uint32_t& r0, uint32_t& r1, uint32_t& r2, uint32_t& r3){
  asm volatile("ldmatrix.sync.aligned.m8n8.x4.shared.b16 {%0,%1,%2,%3}, [%4];":"=r"(r0),"=r"(r1),"=r"(r2),"=r"(r3):"r"(a):"memory"); }
__device__ __forceinline__ void mma_bf16(float (&d)[4], uint32_t a0,uint32_t a1,uint32_t a2,uint32_t a3,uint32_t b0,uint32_t b1){
  asm("mma.sync.aligned.m16n8k16.row.col.f32.bf16.bf16.f32 {%0,%1,%2,%3},{%4,%5,%6,%7},{%8,%9},{%0,%1,%2,%3};"
   :"+f"(d[0]),"+f"(d[1]),"+f"(d[2]),"+f"(d[3]):"r"(a0),"r"(a1),"r"(a2),"r"(a3),"r"(b0),"r"(b1)); }
__device__ __forceinline__ void mma_f16(float (&d)[4], uint32_t a0,uint32_t a1,uint32_t a2,uint32_t a3,uint32_t b0,uint32_t b1){
  asm("mma.sync.aligned.m16n8k16.row.col.f32.f16.f16.f32 {%0,%1,%2,%3},{%4,%5,%6,%7},{%8,%9},{%0,%1,%2,%3};"
   :"+f"(d[0]),"+f"(d[1]),"+f"(d[2]),"+f"(d[3]):"r"(a0),"r"(a1),"r"(a2),"r"(a3),"r"(b0),"r"(b1)); }
__device__ __forceinline__ uint32_t lds32(uint32_t a){ uint32_t v; asm volatile("ld.shared.u32 %0, [%1];":"=r"(v):"r"(a):"memory"); return v; }
__device__ __forceinline__ float lds32f(uint32_t a){ float v; asm volatile("ld.shared.f32 %0, [%1];":"=f"(v):"r"(a):"memory"); return v; }
__device__ __forceinline__ uint32_t lds16(uint32_t a){ uint32_t v; asm volatile("ld.shared.u16 %0, [%1];":"=r"(v):"r"(a):"memory"); return v; }
__device__ __forceinline__ uint2 lds64(uint32_t a){ uint2 v; asm volatile("ld.shared.v2.u32 {%0,%1}, [%2];":"=r"(v.x),"=r"(v.y):"r"(a):"memory"); return v; }
__device__ __forceinline__ void sts16(uint32_t a, uint32_t v){ asm volatile("st.shared.u16 [%0], %1;"::"r"(a),"h"((unsigned short)v):"memory"); }
__device__ __forceinline__ void sts32(uint32_t a, uint32_t v){ asm volatile("st.shared.u32 [%0], %1;"::"r"(a),"r"(v):"memory"); }
__device__ __forceinline__ void sts32f(uint32_t a, float v){ asm volatile("st.shared.f32 [%0], %1;"::"r"(a),"f"(v):"memory"); }
__device__ __forceinline__ void sts64(uint32_t a, uint32_t x, uint32_t y){ asm volatile("st.shared.v2.u32 [%0], {%1,%2};"::"r"(a),"r"(x),"r"(y):"memory"); }
__device__ __forceinline__ void sts128(uint32_t a, uint32_t x, uint32_t y, uint32_t z, uint32_t w){ asm volatile("st.shared.v4.u32 [%0], {%1,%2,%3,%4};"::"r"(a),"r"(x),"r"(y),"r"(z),"r"(w):"memory"); }
__device__ __forceinline__ uint32_t prmt(uint32_t a, uint32_t b, uint32_t s){ uint32_t r; asm("prmt.b32 %0,%1,%2,%3;":"=r"(r):"r"(a),"r"(b),"r"(s)); return r; }
__device__ __forceinline__ uint32_t pack_h2(float lo, float hi){ uint32_t r; asm("cvt.rn.f16x2.f32 %0, %1, %2;":"=r"(r):"f"(hi),"f"(lo)); return r; }
__device__ __forceinline__ uint32_t bf2_mul(uint32_t a, uint32_t b){ uint32_t r; asm("mul.rn.bf16x2 %0,%1,%2;":"=r"(r):"r"(a),"r"(b)); return r; }
__device__ __forceinline__ uint32_t bf2_add(uint32_t a, uint32_t b){ uint32_t r; asm("add.rn.bf16x2 %0,%1,%2;":"=r"(r):"r"(a),"r"(b)); return r; }
__device__ __forceinline__ uint32_t bf2_fma(uint32_t a, uint32_t b, uint32_t c){ uint32_t r; asm("fma.rn.bf16x2 %0,%1,%2,%3;":"=r"(r):"r"(a),"r"(b),"r"(c)); return r; }
__device__ __forceinline__ uint32_t bf_bits(float x){ return pack_bf16(x,0.f)&0xffffu; }
__device__ __forceinline__ void red_relaxed(unsigned* f){ asm volatile("red.relaxed.gpu.global.add.u32 [%0], 1;"::"l"(f):"memory"); }
__device__ __forceinline__ void fence_async_global(){ asm volatile("fence.proxy.async.global;":::"memory"); }
__device__ __forceinline__ void bulk_s2g(void* dst, uint32_t src, uint32_t bytes){ asm volatile("cp.async.bulk.global.shared::cta.bulk_group [%0], [%1], %2;"::"l"(dst),"r"(src),"r"(bytes):"memory"); }
__device__ __forceinline__ void tma_red2(const CUtensorMap* m, int c0, int c1, uint32_t src){
  asm volatile("cp.reduce.async.bulk.tensor.2d.global.shared::cta.add.bulk_group [%0, {%2, %3}], [%1];"::"l"(m),"r"(src),"r"(c0),"r"(c1):"memory"); }
__device__ __forceinline__ void l2_prefetch(const void* p, uint32_t bytes){ asm volatile("cp.async.bulk.prefetch.L2.global [%0], %1;"::"l"(p),"r"(bytes):"memory"); }
__device__ __forceinline__ void bar_arrive_pred(int id, int n, int pred){ asm volatile("{\n.reg .pred p;\nsetp.ne.b32 p, %2, 0;\n@p bar.arrive %0, %1;\n}"::"r"(id),"r"(n),"r"(pred):"memory"); }
__device__ __forceinline__ float sqrt_fast(float x){ float y; asm("sqrt.approx.f32 %0, %1;":"=f"(y):"f"(x)); return y; }
struct cf { float x, y; };
__device__ __forceinline__ cf csq(cf a){ cf r; r.x=fmaf(a.x,a.x,-a.y*a.y); r.y=(a.x+a.x)*a.y; return r; }
__device__ __forceinline__ cf cmul(cf a, cf b){ cf r; r.x=fmaf(a.x,b.x,-a.y*b.y); r.y=fmaf(a.x,b.y,a.y*b.x); return r; }
__device__ __forceinline__ cf cexp_dir(float l2, float turns){
  float r=(turns-__fadd_rn(__fadd_rn(turns,12582912.f),-12582912.f))*6.283185307179586f, m; asm("ex2.approx.ftz.f32 %0, %1;":"=f"(m):"f"(l2));
  cf e; e.x=m*__cosf(r); e.y=m*__sinf(r); return e; }
__device__ __forceinline__ void hmulc(uint32_t re, uint32_t im, uint32_t m, uint32_t& ore, uint32_t& oim){
  __half2 R=*(__half2*)&re, I=*(__half2*)&im, M=*(__half2*)&m; __half2 c=__low2half2(M), d=__high2half2(M);
  __half2 a=__hfma2(c,R,__hneg2(__hmul2(d,I))), b=__hfma2(c,I,__hmul2(d,R)); ore=*(uint32_t*)&a; oim=*(uint32_t*)&b; }

struct Scratch {
  bf16 inbox[128*128*80];
  bf16 x1T[D_*L_];
  bf16 Wp[D_*2*F_];
  bf16 W2p[F_*D_];
  bf16 G[L_*F_];
  float qs[2*F_];
  ulonglong2 st2[8*L_];
  unsigned mod[6*D_];
  unsigned cnt[4*32];
  unsigned gflag[16*32];
};
__device__ __align__(1024) Scratch g_scr;

#define CBM 12
#define CB0 (CBM==12?9:13)
#define HINT_EARLY 0
#define PROMO CU_TENSOR_MAP_L2_PROMOTION_NONE
#define EPI 5
#define REL1 3
#define REL2 3
#define RESAT 26
#define POLLNS 100
#define EPI2 0
#define STP 2
#define PDEPTH 1
#define STNS 100
#define XW 2
#define XF 1
#define STAG 2
#define W1PF 0
#define GATE 2
#define B23 0
#define V4 0
#define W2A 6
#define W2N 3
#define W2PF 1
#define STGA 2
#define NOSYNC 0
#define SPEC 0
#define WFIRST 1
#define W1E 0
#define CNTNS 30
#define EOFF 100
#define WML 1
#define XTE 0
#define PFB 0
#define PFG 0
#define WFST 0
#define GSP 0
#define BPOS 1
#define XRP 0
#define GVP 2
#define CPF 3
#define REDAT 0
#define OUTS 0
#define OUTE 30
#define MAPV 4
#define X_DELAY 200
#define WM_EARLY 1800
#define WM_LATE 3000
constexpr int NSTG = 6, STG = 34816;
constexpr int SM_GS = NSTG*STG, SM_QS = SM_GS+18432, SM_ST = SM_QS+3456, SM_BAR = SM_ST+1024, SM_TOTAL = SM_BAR+400;
constexpr int NST2 = 7, STG2 = 26624, SM_RES = NST2*STG2;
constexpr int KG_WG = 28672, FT_WG = 1664;
constexpr int SM_MI = 0, SM_FT = 5376, SM_PR = SM_FT+4*FT_WG, SM_WM = 17408, SM_KG2 = SM_WM+40960, SM_TB = SM_KG2+KG_WG;
constexpr int SM_XR = SM_TB+3*8192, SM_XS = SM_XR+21504, SM_TB3 = SM_XS+20480, SM_KG = SM_TB3+2*8192;
__device__ __forceinline__ uint32_t tb_off(int ch){ return (ch<3? SM_TB : SM_TB3-3*8192)+ch*8192; }
__device__ __forceinline__ uint32_t kg_off(int wg){ return wg<2? SM_KG+wg*KG_WG : wg==2? SM_KG2 : SM_XS; }
__device__ __forceinline__ int chan(int cta, int i){ return i<3? 3*cta+i : 381+2*cta+i; }
__device__ __forceinline__ int chanw(int cta, int i){ return i<3? ((3*cta)&7)+i : 13+((2*cta)&7)+i; }
constexpr int PLN = 1184, UB = 4*PLN, FPL = 288, FB = 32*FPL, UF = UB+FB;
static_assert(SM_PR%16==0 && SM_PR+5216 <= SM_WM && SM_KG+2*KG_WG==SM_QS && SM_TB3>=4*STG, "front smem");
static_assert(2*UB+2*FB <= KG_WG, "kg alias");

#define TS(k)
#define TSP(k,p)
constexpr int SM_ALLOC = SM_TOTAL;

struct Params {
  const bf16 *in[8];
  const bf16 *x;
  Scratch* s;
  const bf16 *wgp, *wup, *wdp;
  uint32_t zero;
  CUtensorMap wm, xna, xnb, xts, x1red, wg, wu, wps, x1a, x1r, out;
};
__device__ __forceinline__ uint32_t cpz(uint32_t v, uint32_t z){ uint32_t r; asm volatile("xor.b32 %0,%1,%2;":"=r"(r):"r"(v),"r"(z)); return r; }

struct KA { uint32_t er[4], ei[4], hr[4], hi[4], ar[2], ai[2], mH1, m2, m4, m6, m8, m32, m64, mH8; float os; };
__device__ __forceinline__ void kgen_a(KA& k, uint32_t sb, int tl, int ch, int dw, int gate){
  const uint32_t pr=sb+SM_PR+ch*256;
  const float la=bf_lo(lds16(pr+tl*2)), aim=bf_lo(lds16(pr+1280+tl*2));
  const uint2 ma=lds64(pr+2560+(tl&31)*8), mb=lds64(pr+3840+(tl&31)*8);
  cf C; C.x=bf_lo(lds16(pr+2560+tl*2)); C.y=bf_lo(lds16(pr+3840+tl*2));
  asm volatile("{\n.reg .pred p;\nsetp.ne.b32 p, %0, 0;\n@p bar.sync 8, 512;\n}"::"r"(gate):"memory");
  const float dt=bfr(expf(bf_lo(lds16(sb+SM_PR+5120+dw*2))));
  const float l2=bfr(expf(la))*dt*-1.4426950408889634f, tn=aim*dt*0.15915494309189535f;
  uint32_t ex=__vmaxu2(__vmaxu2(ma.x&0x7fff7fffu,ma.y&0x7fff7fffu),__vmaxu2(mb.x&0x7fff7fffu,mb.y&0x7fff7fffu));
  ex=__reduce_max_sync(~0u,max(ex&0xffffu,ex>>16)); ex=min(max(ex>>7,1u),253u);
  { const float sc=__uint_as_float((254u-ex)<<23); C.x*=sc; C.y*=sc; }
  k.os=2.f*dt*__uint_as_float(ex<<23);
  cf E1=cexp_dir(l2,tn), H1=cexp_dir(l2*128.f,tn*128.f);
  cf H2=csq(H1), H4=csq(H2), H8=csq(H4);
  cf E2=csq(E1), E3=cmul(E2,E1), E4=csq(E2), E5=cmul(E4,E1), E6=csq(E3), E7=cmul(E4,E3), E8=csq(E4);
  k.er[0]=pack_h2(E1.x,E2.x); k.er[1]=pack_h2(E3.x,E4.x); k.er[2]=pack_h2(E5.x,E6.x); k.er[3]=pack_h2(E7.x,E8.x);
  k.ei[0]=pack_h2(E1.y,E2.y); k.ei[1]=pack_h2(E3.y,E4.y); k.ei[2]=pack_h2(E5.y,E6.y); k.ei[3]=pack_h2(E7.y,E8.y);
  H8=cmul(H8,E8); k.m8=pack_h2(E8.x,E8.y);
  k.mH1=pack_h2(H1.x,H1.y); k.m2=pack_h2(E2.x,E2.y); k.m4=pack_h2(E4.x,E4.y); k.m6=pack_h2(E6.x,E6.y); k.mH8=pack_h2(H8.x,H8.y);
  {
    E8.y=-E8.y; cf a0; a0.x=C.x; a0.y=-C.y;
    cf E16=csq(E8), a1=cmul(a0,E8), a2=cmul(a0,E16), a3=cmul(a1,E16), E32=csq(E16), E64=csq(E32);
    k.ar[0]=pack_h2(a0.x,a1.x); k.ar[1]=pack_h2(a2.x,a3.x); k.ai[0]=pack_h2(a0.y,a1.y); k.ai[1]=pack_h2(a2.y,a3.y);
    k.m32=pack_h2(E32.x,E32.y); k.m64=pack_h2(E64.x,E64.y); }
  cf H3=cmul(H2,H1), H5=cmul(H4,H1), H6=csq(H3), H7=cmul(H4,H3);
  k.hr[0]=pack_h2(1.f,H1.x); k.hr[1]=pack_h2(H2.x,H3.x); k.hr[2]=pack_h2(H4.x,H5.x); k.hr[3]=pack_h2(H6.x,H7.x);
  k.hi[0]=pack_h2(0.f,H1.y); k.hi[1]=pack_h2(H2.y,H3.y); k.hi[2]=pack_h2(H4.y,H5.y); k.hi[3]=pack_h2(H6.y,H7.y);
}
__device__ __forceinline__ void kgen_b(const KA& k, uint32_t sb, int wg, int warp, int lane){
  const int tl=warp*32+lane;
  const uint32_t wb=sb+kg_off(wg), sa=wb+tl*16;
  { uint32_t a0,a1,a2,a3,b0,b1,b2,b3;
    sts128(sa,k.er[0],k.er[1],k.er[2],k.er[3]); sts128(sa+2048,k.ei[0],k.ei[1],k.ei[2],k.ei[3]);
    hmulc(k.er[0],k.ei[0],k.mH1,a0,b0); hmulc(k.er[1],k.ei[1],k.mH1,a1,b1); hmulc(k.er[2],k.ei[2],k.mH1,a2,b2); hmulc(k.er[3],k.ei[3],k.mH1,a3,b3);
    sts128(sa+2*2048,a0,a1,a2,a3); sts128(sa+3*2048,b0,b1,b2,b3); }
  { uint32_t r2,r3,i2,i3,c0,c1,c2,c3,b0,b1,b2,b3;
    hmulc(k.ar[0],k.ai[0],k.m32,r2,i2); hmulc(k.ar[1],k.ai[1],k.m32,r3,i3);
    sts128(sa+10*2048,k.ar[0],k.ar[1],r2,r3); sts128(sa+11*2048,k.ai[0],k.ai[1],i2,i3);
    hmulc(k.ar[0],k.ai[0],k.m64,c0,b0); hmulc(k.ar[1],k.ai[1],k.m64,c1,b1); hmulc(r2,i2,k.m64,c2,b2); hmulc(r3,i3,k.m64,c3,b3);
    sts128(sa+12*2048,c0,c1,c2,c3); sts128(sa+13*2048,b0,b1,b2,b3); }
  { uint32_t c0,c1,c2,c3,b0,b1,b2,b3;
    hmulc(k.hr[1],k.hi[1],k.m2,c0,b0); hmulc(k.hr[1],k.hi[1],k.m4,c1,b1); hmulc(k.hr[1],k.hi[1],k.m6,c2,b2); hmulc(k.hr[1],k.hi[1],k.m8,c3,b3);
    sts128(sa+4*2048,c0,c1,c2,c3); sts128(sa+5*2048,b0,b1,b2,b3); }
  { uint32_t c0,c1,c2,c3,b0,b1,b2,b3;
    hmulc(k.hr[2],k.hi[2],k.m4,c0,b0); hmulc(k.hr[3],k.hi[3],k.m4,c1,b1); hmulc(k.hr[2],k.hi[2],k.m8,c2,b2); hmulc(k.hr[3],k.hi[3],k.m8,c3,b3);
    sts128(sa+6*2048,c0,c1,c2,c3); sts128(sa+7*2048,b0,b1,b2,b3); }
  { uint32_t c0,c1,c2,c3,b0,b1,b2,b3;
    hmulc(k.hr[0],k.hi[0],k.mH8,c0,b0); hmulc(k.hr[1],k.hi[1],k.mH8,c1,b1); hmulc(k.hr[2],k.hi[2],k.mH8,c2,b2); hmulc(k.hr[3],k.hi[3],k.mH8,c3,b3);
    sts128(sa+8*2048,c0,c1,c2,c3); sts128(sa+9*2048,b0,b1,b2,b3); }
  fence_async_smem();
}
__device__ __forceinline__ void kgen_c(const KA& k, uint32_t sb, uint32_t t0, int wg, int warp, int lane, int ch, int d, int dw, uint32_t zr){
  const float os=k.os;
  const int tl=warp*32+lane;
  const uint32_t wb=sb+kg_off(wg);
  const uint32_t ft=sb+SM_FT+wg*FT_WG+4, R3=ft+1036;
  float acc[8];
  { const uint64_t da=mkdesc(wb+(ch&zr),2048,4096,0), db=da+10*128;
    wg_fence();
    #pragma unroll
    for(int o=0;o<16;o++) wgmma_n16_f16(acc,da+8*o,db+8*o,o>0);
    wg_commit(); }
  const int g=lane>>2, t=lane&3;
  wg_wait<0>(); reg_fence(acc);
  #define DBG(i_,v_)
  if(warp==0){ const uint32_t a=ft+2+(g+16*t)*2;
    #pragma unroll
    for(int i=0;i<8;i++){ const int o=(i&2)*64+8*(8*(i>>2)+(i&1)); const float v=acc[i]*os; DBG(1+g+16*t+o,v); sts16(a+o*2,bf_bits(v)); }
  } else if(warp==1){ const int b0=257+64*(g&1)+(g>>1)+8*t, b1=385+32*(g&3)+(g>>2)+4*t;
    #pragma unroll
    for(int i=0;i<8;i++){ const int n=8*(i>>2)+(i&1), idx=(i&2)? b1+2*n : b0+4*n; const float v=acc[i]*os; DBG(idx,v); sts16(ft+idx*2,bf_bits(v)); }
  } else if(warp==2){ const uint32_t a=R3+(t&1)*256+(31-4*g-(t>>1))*2;
    #pragma unroll
    for(int i=0;i<4;i++){ const float v=acc[(i>>1)*4+(i&1)]*os; DBG(513+16*g+8*(i>>1)+2*t+(i&1),v); sts16(a+(i&1)*128-(i>>1)*4,bf_bits(v)); }
  }
}
__device__ __forceinline__ void tb_zero(uint32_t tb, int tl){
  if(tl<110) sts128(tl<64? tb+4928+(tl>>4)*768+512+(tl&15)*16 : tl<80? tb+(tl-64)*16 : tb+4384+(tl-80)*16,0,0,0,0); }
__device__ __forceinline__ void kgen_t(uint32_t sb, int wg, int warp, int lane, int ch){
  const int tl=warp*32+lane;
  const uint32_t ft=sb+SM_FT+wg*FT_WG+4, R3=ft+1036;
  const uint32_t P=sb+tb_off(ch)+256, T3=P+4672;
  { const uint32_t ta=R3+warp*128+(lane>>1)*4, sh=(lane&1)*16;
    uint32_t a0=lds32(ft+tl*4), a1=lds32(ft+tl*4-4), c0=lds32(ft+512+tl*4), c1=lds32(ft+516+tl*4), e=lds16(ft+1024);
    uint32_t v0=lds32(ta), v1=lds32(ta+4), v2=lds32(ta+8), v3=lds32(ta+12), v4=lds32(ta+16);
    uint32_t pm=0; if(tl==0){ pm=lds32(ft+508); a0=prmt(a0,lds32(sb+SM_MI+5120+ch*4),0x3254); a1=0; }
    sts64(P+tl*8, prmt(a0,a1,0x7610), prmt(a0,a0,0x1032));
    const uint32_t ll=prmt(c0,c0,0x1010), hl=prmt(c0,c0,0x1032), nh=prmt(c0,c1,0x3254);
    if(warp<2) sts128(P+1024+tl*16, tl? ll : prmt(c0,pm,0x7610), ll, hl, nh);
    else { const uint32_t hh=prmt(c0,c0,0x3232), nn=prmt(c1,c1,0x1010);
      sts128(P+tl*32, ll,ll,ll,hl); sts128(P+tl*32+16, hh,hh,nh,nn); }
    if(tl<8) sts32(P+4096+tl*4, tl<5? (e|(e<<16)) : (tl==5? e<<16 : 0u));
    if(ch==3) tb_zero(P-256,tl);
    sts128(T3+warp*768+lane*16, __funnelshift_r(v0,v1,sh), __funnelshift_r(v1,v2,sh), __funnelshift_r(v2,v3,sh), __funnelshift_r(v3,v4,sh));
  }
}

template<int NS> __device__ __forceinline__ void conv_load(uint32_t (&v)[17], uint32_t pp){
  #pragma unroll
  for(int i=0;i<2*NS+1;i++) v[i]=lds32(pp+(i-1)*32);
}
template<int N,int NS> __device__ __forceinline__ void conv_issue(float (&c)[32], const uint32_t (&w)[17], uint64_t db, int acc, uint32_t zr){
  uint32_t v[2*NS+1];
  #pragma unroll
  for(int i=0;i<2*NS+1;i++) v[i]= V4? cpz(w[i],zr) : w[i];
  wg_fence();
  #pragma unroll
  for(int i=0;i<NS;i++){ const int o=(2-2*(i&1))*(PLN/16)+(i>>1);
    if constexpr(N==64) wgmma_n64_rs(c, v[2*i+1],v[2*i+2],v[2*i],v[2*i+1], db+o, i>0 || acc);
    else if constexpr(N==48) wgmma_n48_rs(c, v[2*i+1],v[2*i+2],v[2*i],v[2*i+1], db+o, 1);
    else wgmma_n32_rs(c, v[2*i+1],v[2*i+2],v[2*i],v[2*i+1], db+o, 1); }
}
__device__ __forceinline__ void rx_store(uint32_t sb, const bf16* inbox, int ch, int d, uint32_t TG, uint32_t U, int tl, uint32_t t0){
  const int st= ch<3? 96:64, o=(tl>>1)*st+(ch<3? 0:12192)+ch*32+((tl^(d>>2))&1)*16;
  uint4 v[2]={lds128(sb+SM_XR+o), lds128(sb+SM_XR+64*st+o)};
  const uint2 sc=lds64(sb+SM_MI+5152+ch*8);
  while(true){
    #pragma unroll
    for(int q=0;q<2;q++){ v[q].x^=TG; v[q].y^=TG; v[q].z^=TG; v[q].w^=TG; }
    if(!__any_sync(~0u,(v[0].x|v[0].y|v[0].z|v[0].w|v[1].x|v[1].y|v[1].z|v[1].w)&0x40004000u)) break;
    if(__any_sync(~0u,(int)(clk32()-t0)<0)) break;
    #pragma unroll
    for(int q=0;q<2;q++) asm volatile("ld.relaxed.gpu.global.v4.u32 {%0,%1,%2,%3}, [%4];":"=r"(v[q].x),"=r"(v[q].y),"=r"(v[q].z),"=r"(v[q].w):"l"((const unsigned char*)inbox+o+q*64*st):"memory"); }
  #pragma unroll
  for(int q=0;q<2;q++) sts128(U+(tl&3)*PLN+(63-32*q-(tl>>2))*16, bf2_add(bf2_mul(v[q].x,sc.x),sc.y), bf2_add(bf2_mul(v[q].y,sc.x),sc.y), bf2_add(bf2_mul(v[q].z,sc.x),sc.y), bf2_add(bf2_mul(v[q].w,sc.x),sc.y));
}
__device__ __forceinline__ void box_filter(uint32_t U, int tl){
  const uint32_t Fb=U+UB; const int q0=tl+2, q1=tl+3, q2=tl+4;
  uint2 lo=lds64(U+(q0&3)*PLN+(64-(q0>>2))*16+8); uint4 mid=lds128(U+(q1&3)*PLN+(64-(q1>>2))*16); uint2 hi=lds64(U+(q2&3)*PLN+(64-(q2>>2))*16);
  uint32_t w[8]={lo.x,lo.y,mid.x,mid.y,mid.z,mid.w,hi.x,hi.y}; float u[16];
  #pragma unroll
  for(int i=0;i<8;i++){ u[2*i]=bf_lo(w[i]); u[2*i+1]=bf_hi(w[i]); }
  float s7[8], s9[8];
  s7[0]=((u[1]+u[2])+(u[3]+u[4]))+((u[5]+u[6])+u[7]);
  #pragma unroll
  for(int i=1;i<8;i++) s7[i]=s7[i-1]+(u[i+7]-u[i]);
  #pragma unroll
  for(int i=0;i<8;i++) s9[i]=s7[i]+(u[i]+u[i+8]);
  const uint32_t a[8]={pack_bf16(s7[0],s7[1]),pack_bf16(s7[2],s7[3]),pack_bf16(s7[4],s7[5]),pack_bf16(s7[6],s7[7]),
                       pack_bf16(s9[0],s9[1]),pack_bf16(s9[2],s9[3]),pack_bf16(s9[4],s9[5]),pack_bf16(s9[6],s9[7])};
  #pragma unroll
  for(int c=0;c<4;c++){ const int q=tl+c;
    if(q<128) sts128(Fb+(c*8+((q>>3)&4)+(q&3))*FPL+((q>>6)*8+((q>>2)&7))*16, a[4*(c&1)],a[4*(c&1)+1],a[4*(c&1)+2],a[4*(c&1)+3]); }
}

__device__ __forceinline__ void mod_gemv(const Params& p, uint32_t sb, int cta, int wg, int warp, int lane, uint32_t tag16, uint32_t t0){
      const uint32_t MI=sb+SM_MI, wmb=sb+SM_BAR+176; const int g=lane>>2, t=lane&3, mi=lane>>3, lead=(warp|lane)==0; (void)lead;
      const uint32_t toff=warp*10240+((mi>>1)*8+(lane&7))*64, tsw=(lane>>1)&3;
      uint32_t bv[20];
      #pragma unroll
      for(int k=0;k<20;k++) bv[k]=lds32(MI+(warp*160+k*8+2*t)*2);
      mbar_wait(wmb,0,t0);
      TSP(15,lead);
      float c0[4]={0,0,0,0}, c1[4]={0,0,0,0};
      { float e0[4]={0,0,0,0}, e1[4]={0,0,0,0};
        #pragma unroll
        for(int hf=0;hf<2;hf++){ uint32_t a[40];
          #pragma unroll
          for(int k=0;k<5;k++){ uint32_t ad=sb+SM_WM+toff+(hf*5+k)*1024;
            ldsm4t(ad+(((mi&1)^tsw)<<4),a[8*k],a[8*k+1],a[8*k+2],a[8*k+3]); ldsm4t(ad+(((2+(mi&1))^tsw)<<4),a[8*k+4],a[8*k+5],a[8*k+6],a[8*k+7]); }
          #pragma unroll
          for(int k=0;k<5;k++){ const int kk=hf*5+k;
            if(kk&1){ mma_bf16(e0,a[8*k],a[8*k+1],a[8*k+2],a[8*k+3],bv[2*kk],bv[2*kk+1]); mma_bf16(e1,a[8*k+4],a[8*k+5],a[8*k+6],a[8*k+7],bv[2*kk],bv[2*kk+1]); }
            else { mma_bf16(c0,a[8*k],a[8*k+1],a[8*k+2],a[8*k+3],bv[2*kk],bv[2*kk+1]); mma_bf16(c1,a[8*k+4],a[8*k+5],a[8*k+6],a[8*k+7],bv[2*kk],bv[2*kk+1]); } } }
        c0[0]+=e0[0]; c0[2]+=e0[2]; c1[0]+=e1[0]; c1[2]+=e1[2]; }
      if(t==0){ uint32_t a=MI+2560+warp*128+g*4; sts32f(a,c0[0]); sts32f(a+32,c0[2]); sts32f(a+64,c1[0]); sts32f(a+96,c1[2]); }
      bar_sync(1+wg,128);
      if(warp==1){ uint32_t a=MI+2560+lane*4; float s=(lds32f(a)+lds32f(a+128))+(lds32f(a+256)+lds32f(a+384));
        asm volatile("st.relaxed.gpu.global.u32 [%0], %1;"::"l"(p.s->mod+cta*32+lane),"r"((bf_bits(s)<<16)|tag16):"memory"); }
      TSP(16,warp==1 && lane==0);
}

__device__ __forceinline__ void fetch_inbox(const Params& p, uint32_t sb, int cta, int lane, unsigned ep, uint32_t tag16, uint32_t t0){
  const uint32_t gateb=sb+SM_BAR+192; const unsigned* hp=p.s->cnt+96+(lane&p.zero);
  const unsigned* mp=p.s->mod+((lane&1)^1)*D_+chan(cta,min(lane>>1,4));
  unsigned h=ld_relaxed(hp); uint32_t v=ld_relaxed(mp);
  if(SPEC){ if(elect_one()){ bulk_wait0_read();
      TS(78); mbar_expect_tx(gateb,12288); bulk_g2s(sb+SM_XR,p.s->inbox+(size_t)cta*128*80,12288,gateb); }
    __syncwarp(); }
  if(!SPEC || __any_sync(~0u,(int)(h-(ep+1)*128u)<0)){
    while(__any_sync(~0u,(int)(h-(ep+1)*128u)<0 && (int)(clk32()-t0)>=0)){ __nanosleep(20); h=ld_relaxed(hp); }
    if(elect_one()){ TS(97);
      if(SPEC) asm volatile("mbarrier.expect_tx.relaxed.cta.shared::cta.b64 [%0], %1;"::"r"(gateb),"r"(12288):"memory");
      else { bulk_wait0_read(); mbar_expect_tx(gateb,12288); }
      bulk_g2s(sb+SM_XR,p.s->inbox+(size_t)cta*128*80,12288,gateb); }
    __syncwarp(); }
  { v^=tag16;
    while(__any_sync(~0u,(v&0xffffu) && (int)(clk32()-t0)>=0)){ __nanosleep(40); v=ld_relaxed(mp)^tag16; }
    const float cs=bfr(1.f+__uint_as_float(v))*4294967296.f;
    v=(lane&1)? v|(v>>16) : pack_bf16(cs,cs);
    if(lane<10) sts32(sb+SM_MI+5152+lane*4,v); }
  __syncwarp(); mbar_arrive_pred(gateb,1,lane==0);
}

template<int PACE> __device__ __forceinline__ void geglu(float (&acc0)[72], float (&acc1)[72], uint32_t sb, int sub, int warp, int lane, uint32_t zr){
  const int g=lane>>2, t=lane&3;
  float rs[4], rh[4];
  #pragma unroll
  for(int r=0;r<4;r++){ rs[r]=lds32f(sb+SM_ST+((r>>1)*64+warp*16+(r&1)*8+g)*4); rh[r]=0.5f*rs[r]; }
  const uint32_t qa=sb+SM_QS+(sub*72+2*t)*8;
  const uint32_t ga=sb+SM_GS+(((lane>>4)*64)+warp*16+((lane>>3)&1)*8+(lane&7))*16;
  float4 q0, n0;
  if(PACE==0 || PACE==5 || PACE==6) q0=lds128f(qa);
  #pragma unroll
  for(int i=0;i<9;i++){
    if(PACE==0 || PACE==5 || PACE==6){ if(i<8) n0=lds128f(qa+i*64+64); }
    else q0=lds128f(qa+i*64);
    uint32_t o[4];
    #pragma unroll
    for(int r=0;r<4;r++){
      float res[2];
      #pragma unroll
      for(int e=0;e<2;e++){
        float ag = (r>>1)? acc1[8*i+(r&1)*2+e] : acc0[8*i+(r&1)*2+e];
        float au = (r>>1)? acc1[8*i+4+(r&1)*2+e] : acc0[8*i+4+(r&1)*2+e];
        float gv = fmaf(rs[r], ag, e? q0.z:q0.x);
        float uv = fmaf(rh[r], au, e? q0.w:q0.y);
        float z = gv*fmaf(gv*gv, 0.044715f*0.7978845608f, 0.7978845608f);
        float pr = gv*uv;
        res[e] = fmaf(pr, tanh_fast(z), pr);
      }
      o[r]=pack_bf16(res[0],res[1]);
      if(PACE==3 || PACE==6) rs[(r+1)&3]=__uint_as_float(__float_as_uint(rs[(r+1)&3])|(o[r]&zr));
      if((PACE==4 || PACE==5) && (r&1)){ rs[(r+1)&3]=__uint_as_float(__float_as_uint(rs[(r+1)&3])|(o[r-1]&zr)); rs[(r+2)&3]=__uint_as_float(__float_as_uint(rs[(r+2)&3])|(o[r]&zr)); }
    }
    stsm4(ga+i*2048,o[0],o[1],o[2],o[3]);
    if(PACE==0 || PACE==5 || PACE==6) q0=n0;
    if(i==4){ fence_async_smem(); bar_arrive(11,160); }
  }
}

template<bool BYSM> __global__ void __launch_bounds__(512,1) fused_kernel(const __grid_constant__ Params p){
  extern __shared__ __align__(1024) unsigned char smem[];
  const uint32_t sb = opaque(smem_u32(smem));
  const uint32_t t0 = clk32();
  const int tid=threadIdx.x, lane=tid&31, tl=tid&127;
  const int wid=__shfl_sync(~0u,tid>>5,0), wg=wid>>2, warp=wid&3;
  int cta;
  if(BYSM){ asm volatile("mov.u32 %0, %%smid;":"=r"(cta)); cta= cta<120? cta : cta<124? cta+8 : cta-4; } else cta=blockIdx.x;
  if(cta>=128){
    const uint32_t bar=sb+SM_BAR; const int e=cta-128, n=(54-e+3)>>2;
    const unsigned char* src=(const unsigned char*)p.wdp+e*40960;
    __nanosleep(1500);
    if(wid==0){ if(elect_one()){
      #pragma unroll 1
      for(int i=0;i<3;i++){ mbar_init(bar+8*i,1); mbar_expect_tx(bar+8*i,40960); bulk_g2s(sb+i*40960,src+(size_t)i*163840,40960,bar+8*i); } }
      __syncwarp(); }
    __syncthreads();
    int s=0, ph=0;
    #pragma unroll 1
    for(int i=0;i<n;i++){
      mbar_wait(bar+8*s,ph,t0);
      const uint32_t ob=sb+122880+(i&1)*40960; uint4 v[5];
      #pragma unroll
      for(int k=0;k<5;k++){ const int u=(tid>>3)+64*k, kb=u/80, c=((u%80)&~7)+((u+lane)&7); v[k]=lds128(sb+s*40960+kb*10240+(lane&7)*1280+c*16); }
      if(wid==0){ if(elect_one()) asm volatile("cp.async.bulk.wait_group.read 1;":::"memory"); __syncwarp(); }
      __syncthreads();
      #pragma unroll
      for(int k=0;k<5;k++){ const int u=(tid>>3)+64*k, kb=u/80, c=((u%80)&~7)+((u+lane)&7); sts128(ob+(c/10)*5120+kb*1280+(c%10)*128+(lane&7)*16,v[k].x,v[k].y,v[k].z,v[k].w); }
      fence_async_smem();
      __syncthreads();
      if(wid==0){ if(elect_one()){
        if(i+3<n){ mbar_expect_tx(bar+8*s,40960); bulk_g2s(sb+s*40960,src+(size_t)(i+3)*163840,40960,bar+8*s); }
        #pragma unroll 1
        for(int jj=0;jj<8;jj++) bulk_s2g((unsigned char*)p.s->W2p+(size_t)jj*276480+(i*4+e)*5120,ob+jj*5120,5120);
        bulk_commit(); }
        __syncwarp(); }
      if(++s==3){ s=0; ph^=1; } }
    if(wid==0){ if(elect_one()){ bulk_wait0(); red_relaxed(p.s->cnt+64); } __syncwarp(); }
    return; }
  const int g=lane>>2, t=lane&3;
  const int lead = tl==0;
  const uint32_t fullb=sb+SM_BAR, emptyb=fullb+64, gsb=fullb+128, depb=fullb+136, xb=fullb+168, wmb=fullb+176, w1b=fullb+184, gateb=fullb+192, r1b=fullb+216, prb=fullb+224, cb_=fullb+200, fb_=fullb+48, full2=fullb+256, empty2=fullb+320, resb=fullb+312, rxb=fullb+376, locb=fullb+384;
  const uint32_t MI=sb+SM_MI;
  if(wid<5){ if(elect_one()){
    if(wid<4){ const uint32_t bar=prb+8*wid; const bf16* src=p.in[wid]; mbar_init(bar,1); mbar_expect_tx(bar,wid<2? 1312:1296);
      bulk_g2s(sb+SM_PR+wid*1280,src+cta*3*N_,768,bar); bulk_g2s(sb+SM_PR+wid*1280+768,src+(384+cta*2)*N_,512,bar);
      bulk_g2s(sb+SM_PR+5120+(wid&1)*48+(wid>>1)*32,p.in[4+(wid&1)]+((wid<2? 3*cta : 384+2*cta)&~7),wid<2? 32:16,bar); }
    else { mbar_init(xb,2); mbar_init(cb_,1); mbar_init(wmb,1); mbar_init(gateb,2); mbar_expect_tx(xb,20480); mbar_expect_tx(cb_,1280); mbar_expect_tx(wmb,40960); }
    } __syncwarp(); }
  __syncthreads();
  if(wid>=8){
    if(X_DELAY){ const uint32_t t1=clk32(); while((int)(clk32()-t1) < X_DELAY); }
    if(elect_one()){
    const bf16* src=p.x+(size_t)(cta*16+(wid-8)*2)*D_; const uint32_t dst=sb+SM_XR+(wid-8)*2592;
    if(wid==12) bulk_g2s(MI+1280,p.in[6],1280,cb_);
    bulk_g2s(dst,src,1280,xb); bulk_g2s(dst+1296,src+D_,1280,xb);
    if(wid==13){ prefetch_tmap(&p.wm); prefetch_tmap(&p.xna); prefetch_tmap(&p.xnb); prefetch_tmap(&p.xts); }
    } __syncwarp(); }
  else if(wid==3){ if(elect_one()){ sts32(fullb+208,ld_relaxed(p.s->cnt)); mbar_arrive_pred(xb,1,1); } __syncwarp(); }
  if(wg!=3) tb_zero(sb+tb_off(wg),tl); else { tb_zero(sb+tb_off(4),tl); if(tl>=112) sts128(sb+SM_FT+((tl>>2)&3)*FT_WG+1040+(tl&3)*128+64,0,0,0,0); }
  KA ka;
  TSP(82,tid==96);
  mbar_wait(prb,0,t0); mbar_wait(prb+8,0,t0); mbar_wait(prb+16,0,t0); mbar_wait(prb+24,0,t0);
  TSP(1,tid==96);
  if(wid==5 && cta<(WML? 40:120)){ if(elect_one()){
    #pragma unroll
    for(int i=0;i<4;i++) tma_ld2(sb+SM_WM+i*10240,&p.wm,cta*32,i*160,wmb);
    } __syncwarp(); }
  if(wid<5){
    const uint2 c=lds64(sb+SM_PR+2560+wid*256+lane*8); const int dw=chanw(cta,wid);
    float f0=(bf_lo(c.x)+bf_hi(c.x))+(bf_lo(c.y)+bf_hi(c.y));
    #pragma unroll
    for(int o=16;o;o>>=1) f0+=__shfl_xor_sync(~0u,f0,o);
    f0*=2.f*bfr(expf(bf_lo(lds16(sb+SM_PR+5120+dw*2))));
    if(lane==0) sts32(MI+5120+wid*4,bf_bits(f0+bf_lo(lds16(sb+SM_PR+5168+dw*2)))); }
  if(wg<2) bar_arrive(7,512);
  kgen_a(ka,sb,tl,wg,chanw(cta,wg),STGA && wg<2);
  if(STGA==1) bar_arrive_pred(8|((ka.m64|ka.hr[3]|ka.ai[1]|ka.er[3])&p.zero),512,wg>=2);
  kgen_b(ka,sb,wg,warp,lane);
  if(STGA==2) bar_arrive_pred(8,512,wg>=2);
  TSP(60,tid==0); TSP(2,tid==256);
  if(wg<2){
    mbar_wait(xb,0,t0);
    if(wg==0){ if(elect_one()){
      if(warp==0){ for(int i=0;i<NSTG;i++){ mbar_init(fullb+8*i,1); mbar_init(emptyb+8*i,5); } }
      else if(warp==1){ mbar_init(fb_,1); mbar_init(fb_+8,1); mbar_init(emptyb+48,1); mbar_init(emptyb+56,1); mbar_init(gsb,1);
        for(int i=0;i<4;i++) mbar_init(depb+8*i,1);
        mbar_init(w1b,1); mbar_init(r1b,2); }
      else if(warp==2){ for(int i=0;i<NST2;i++) mbar_init(full2+8*i,1); mbar_init(resb,1);  }
      else { for(int i=0;i<NST2;i++) mbar_init(empty2+8*i,1); mbar_init(rxb,1);
      } } __syncwarp(); }
    if(PFB && wid==1){ if(elect_one()){ l2_prefetch((const unsigned char*)p.wgp+(size_t)cta*PFB,PFB); l2_prefetch((const unsigned char*)p.wup+(size_t)cta*PFB,PFB); } __syncwarp(); }
    if(wg==1){
      mbar_wait(cb_,0,t0);
      uint32_t cv[5];
      #pragma unroll
      for(int i=0;i<5;i++) cv[i]=lds16(MI+1280+(warp*160+lane+32*i)*2);
      #pragma unroll
      for(int i=0;i<5;i++){ float x=bf_lo(cv[i]); sts16(MI+(warp*160+lane+32*i)*2, bf_bits(__fdividef(x,1.f+__expf(-x)))); }
      __syncwarp();
      if(cta<120) mod_gemv(p,sb,cta,wg,warp,lane,(lds32(fullb+208)>>8)%65535u+1,t0);
      }
    bar_arrive(9,384);
  } else {
    if(WML && wid==13 && cta>=40 && cta<120){ if(elect_one()){
      #pragma unroll
      for(int i=0;i<4;i++) tma_ld2(sb+SM_WM+i*10240,&p.wm,cta*32,i*160,wmb);
      } __syncwarp(); }
    bar_sync(1+wg,128);
    kgen_c(ka,sb,t0,wg,warp,lane,wg,chan(cta,wg),chanw(cta,wg),p.zero);
    uint32_t xv[20];
    mbar_wait(xb,0,t0);
    TSP(13,tid==384);
    const int w8=wid-8;
    const uint32_t xa=sb+SM_XR+(lane&15)*1296+(w8*80+(lane>>4)*8)*2;
    #pragma unroll
    for(int k=0;k<5;k++) ldsm4(xa+k*32,xv[4*k],xv[4*k+1],xv[4*k+2],xv[4*k+3]);
    const uint32_t tg2=(lds32(fullb+208)>>8)%3u+1;
    const int chl=w8*80+(lane>>4)*8+(lane&7), hh=(lane>>3)&1;
    const uint32_t so=chl*32+((hh^((chl>>2)&1))<<4), na=sb+SM_XR+so;
    { float c1[4]={0,0,0,0}, c2[4]={0,0,0,0}, c3[4]={0,0,0,0};
      #pragma unroll
      for(int k=0;k<5;k++){ const uint32_t* a=xv+4*k;
        mma_bf16(c1,a[0],a[1],a[2],a[3],a[0],a[2]); mma_bf16(c2,a[0],a[1],a[2],a[3],a[1],a[3]); mma_bf16(c3,a[0],a[1],a[2],a[3],0x3f803f80u,0x3f803f80u); }
      if(t==(g>>1)) sts128f(MI+3840+w8*128+g*16, make_float4(c3[0],(g&1)?c1[1]:c1[0],c3[2],(g&1)?c2[3]:c2[2])); }
    TSP(86,tid==384);
    bar_sync(13,256);
    uint32_t nm[2], r2h[2], r2l[2];
    { float4 q0=lds128f(MI+3840+t*256+g*16), q1=lds128f(MI+3840+t*256+128+g*16);
      float a=q0.x+q1.x, b=q0.y+q1.y, c=q0.z+q1.z, e=q0.w+q1.w;
      float su=((t&2)?c:a)+__shfl_xor_sync(~0u,(t&2)?a:c,2), sq=((t&2)?e:b)+__shfl_xor_sync(~0u,(t&2)?b:e,2);
      su+=__shfl_xor_sync(~0u,su,1); sq+=__shfl_xor_sync(~0u,sq,1);
      const float mu=su*(1.f/D_), var=bfr(fmaxf(sq*(1.f/D_)-mu*mu,0.f));
      const float rr=__fdividef(2.3283064365386963e-10f,bfr(sqrt_fast(bfr(var+1e-5f))));
      const uint32_t w1=pack_bf16(-mu,rr), w2=pack_bf16(rr-bf_hi(w1),0.f);
      const uint32_t o1=__shfl_xor_sync(~0u,w1,2), o2=__shfl_xor_sync(~0u,w2,2);
      const uint32_t a1=(t&2)?o1:w1, a2=(t&2)?o2:w2, b1=(t&2)?w1:o1, b2=(t&2)?w2:o2;
      nm[0]=prmt(a1,a1,0x1010); r2h[0]=prmt(a1,a1,0x3232); r2l[0]=prmt(a2,a2,0x1010);
      nm[1]=prmt(b1,b1,0x1010); r2h[1]=prmt(b1,b1,0x3232); r2l[1]=prmt(b2,b2,0x1010); }
    const uint32_t TT=((tg2>>(g&1))&1)*0x40004000u;
    #pragma unroll
    for(int k=0;k<5;k++){ uint32_t o[4];
      #pragma unroll
      for(int i=0;i<4;i++){ uint32_t dd=bf2_add(xv[4*k+i],nm[i&1]); o[i]=bf2_fma(dd,r2h[i&1],bf2_mul(dd,r2l[i&1]))|TT; }
      stsm4t(na+k*512,o[0],o[1],o[2],o[3]); }
    fence_async_smem();
    if(wg==2) bar_arrive(14,256); else bar_sync(14,256);
    if(wid==12){ if(elect_one()){ tma_st2(&p.xna,cta*48,0,sb+SM_XR); bulk_commit();
      red_relaxed(p.s->cnt+96);
      TS(14); } __syncwarp(); }
    if(BPOS==0 && wid==13){ if(elect_one()){ tma_st2(&p.xnb,6144+cta*32,0,sb+SM_XR+12288); bulk_commit(); } __syncwarp(); }
    if(GATE==1) bar_arrive(15,512);
    { const uint32_t ra=sb+SM_XS+so;
      #pragma unroll
      for(int k=0;k<5;k++) stsm4t(ra+k*512,xv[4*k],xv[4*k+1],xv[4*k+2],xv[4*k+3]); }
    bar_sync(7,512);
    kgen_t(sb,wg,warp,lane,wg);
    fence_async_smem();
    if(GATE==2) bar_arrive(15,512);
    if(wg==2){ bar_arrive(13,256);
      kgen_a(ka,sb,tl,4,chanw(cta,4),0); kgen_b(ka,sb,2,warp,lane); }
  }
  const int mi=lane>>3;
  const uint32_t toff=warp*10240+((mi>>1)*8+(lane&7))*64, tsw=(lane>>1)&3;
  const unsigned cnt0=lds32(fullb+208), ep=cnt0>>8; const uint32_t tag16=ep%65535u+1;
  const int wsl= cta<36? cta : (cta>=40 && cta<112)? cta-4 : -1, mat=wsl&1, sl=wsl>>1;
  const uint32_t kb=sb+kg_off(wg);
  if(wg<3){
    if(wg<2 && GATE) bar_sync(15,512); else bar_sync(1+wg,128);
    const int ch= wg<2? wg : 4;
    kgen_c(ka,sb,t0,wg,warp,lane,ch,chan(cta,ch),chanw(cta,ch),p.zero);
    bar_sync(1+wg,128);
    kgen_t(sb,wg,warp,lane,ch); TSP(3,tid==0); TSP(76,tid==256);
  } else {
    bar_sync(9,384);
    if(W1E==2 || (W1E==1 && cta<36)){ if(warp==2 && wsl>=0){ if(elect_one()){ mbar_expect_tx(w1b,40960);
        #pragma unroll 1
        for(int i=0;i<4;i++) tma_ld2(sb+SM_WM+i*10240,mat?&p.wu:&p.wg,sl*32,i*160,w1b);
        } __syncwarp(); }
    }
    bar_sync(13,256);
    if(XTE){ if(warp==1){ if(elect_one()){
        #pragma unroll 1
        for(int i=0;i<4;i++) tma_st2(&p.xts,cta*16,i*160,sb+SM_XS+i*5120);
        bulk_commit(); } __syncwarp(); } }
    if(BPOS==1 && warp==1){ if(elect_one()){ tma_st2(&p.xnb,6144+cta*32,0,sb+SM_XR+12288); bulk_commit(); } __syncwarp(); }
    if(warp==0) fetch_inbox(p,sb,cta,lane,ep,tag16,t0);
  }
  uint32_t mv[10];
  { const bf16* inbox=p.s->inbox+(size_t)cta*128*80;
    const uint32_t tg2=ep%3u+1, TG=((tg2&1)<<14)|((tg2>>1)<<30);
    if(wg<3){
      if(tl<56){ uint32_t a= tl<40? kb+(tl&3)*PLN+(64+(tl>>2))*16 : kb+UB+(((tl-40)>>2)*8+(tl&3))*FPL; sts128(a,0,0,0,0); if(wg<2) sts128(a+UF,0,0,0,0); }
      mbar_wait(gateb,0,t0);
      TSP(83,tid==0);
      rx_store(sb,inbox,wg,chan(cta,wg),TG,kb,tl,t0);
      fence_async_smem();
      bar_arrive(12,512);
      if(wg<2){ bar_arrive(10,384); bar_sync(1+wg,128); } else bar_sync(10,384);
      TSP(4,tid==0); TSP(12,tid==128);
    } else {
      while(true){ uint32_t bad=0;
        #pragma unroll
        for(int i=0;i<10;i++) mv[i]=ld_relaxed(p.s->mod+3*D_+tl+128*i);
        #pragma unroll
        for(int i=0;i<10;i++){ mv[i]^=tag16; bad|=mv[i]; }
        if(!__any_sync(~0u,bad&0xffffu)) break;
        if(__any_sync(~0u,(int)(clk32()-t0)<0)) break;
        __nanosleep(200); }
      #pragma unroll
      for(int i=0;i<5;i++){ const int d=tl+128*i, q=d/160, k=d-160*q; const uint32_t a=MI+1280+(k>>3)*128+q*32+(k&7)*2;
        sts16(a,mv[i]>>16); sts16(a+16,bf_bits(1.f+__uint_as_float(mv[5+i]))); }
      mbar_wait(gateb,0,t0);
      if(warp==1){ if(elect_one()){
        bulk_wait0_read(); mbar_expect_tx(prb+16,8192); bulk_g2s(sb+SM_XR+12288,p.s->inbox+(size_t)cta*128*80+6144,8192,prb+16);
        if(PFG){ l2_prefetch((const unsigned char*)p.wgp+128*PFB+(size_t)cta*(17280-PFB),17280-PFB); l2_prefetch((const unsigned char*)p.wup+128*PFB+(size_t)cta*(17280-PFB),17280-PFB); }
        #pragma unroll 1
        for(int ph=0;ph<2;ph++){
          if(ph==WFST){
            #pragma unroll 1
            for(int i=0;i<4;i++) tma_st2(&p.xts,cta*16,i*160,sb+SM_XS+i*5120);
            bulk_commit(); }
          else if(wsl>=0){ mbar_expect_tx(w1b,40960);
            #pragma unroll 1
            for(int i=0;i<4;i++) tma_ld2(sb+SM_WM+i*10240,mat?&p.wu:&p.wg,sl*32,i*160,w1b); } }
        } __syncwarp(); }
      TSP(84,lead);
      if(XTE && warp==1){ if(elect_one()){ bulk_wait0(); red_relaxed(p.s->cnt+32); TS(18); } __syncwarp(); }
      bar_sync(12,512);
    }
    if(wg==STAG || (STAG==1 && wg==2)){
      #pragma unroll 1
      for(int i=(wg==1);i<(wg==1? 2:3);i+=(STAG==1? 2:1)) box_filter(sb+kg_off(i),tl);
      fence_async_smem();
      bar_sync(1+wg,128);
      mbar_arrive_pred(fb_,1,lead && wg>=2);
      TSP(79,lead && wg>=2);
    }
    if(wg==3){
      mbar_wait(prb+16,1,t0);
      #pragma unroll 1
      for(int i=0;i<2;i++) rx_store(sb,inbox,3+i,chan(cta,3),TG,sb+SM_KG+i*KG_WG+UF,tl,t0);
      if(XRP==0 || wsl<0){ if(warp==1){ if(elect_one()){ bulk_wait0(); red_relaxed(p.s->cnt+32); TS(18); } __syncwarp(); } }
      fence_async_smem();
      bar_sync(4,128);
      mbar_arrive_pred(rxb,1,lead);
    } }
  if(wg<3){
    #pragma unroll 1
    for(int ch=wg; ch<5; ch+=3){
      const int it=ch>=3;
      const uint32_t U=kb+it*UF, TB=sb+tb_off(ch);
      uint32_t pp=TB+256+(16*(warp&1)+256*(warp>>1)+g-2*t-16)*4;
      uint64_t db=mkdesc(U,PLN,128,0);
      float c[32];
      if(it) mbar_wait(rxb,0,t0);
      uint32_t w[17];
      const uint32_t p3= warp<2? pp+4096 : TB+256+1056*4;
      if(V4) conv_load<8>(w,pp);
      #pragma unroll 1
      for(int b=0;b<2;b++){
        if(!V4) conv_load<8>(w,pp);
        conv_issue<64,8>(c,w,db,b,p.zero); wg_commit();
        pp+= b? 1536:512; db+= b? 12:4;
        if(it && b==REDAT && warp==0){ if(elect_one()){ bulk_wait0(); red_relaxed(p.s->cnt+EOFF); } __syncwarp(); }
        wg_wait<0>(); TSP(68+b+4*it,tid==0); }
      uint32_t gv=0, xc=0;
      asm volatile("{\n.reg .pred q;\nsetp.ne.b32 q, %2, 0;\n@q ld.relaxed.gpu.global.u32 %0, [%1];\n}":"+r"(gv):"l"(p.s->mod+2*D_+chan(cta,ch)+lane),"r"((int)(lane==0)):"memory");
      if(GVP==0) asm volatile("{\n.reg .pred q;\nsetp.ne.b32 q, %2, 0;\n@q ld.relaxed.gpu.global.u32 %0, [%1];\n}":"+r"(xc):"l"(p.s->cnt+32+lane),"r"((int)(lead)):"memory");
      #pragma unroll 1
      for(int b=0;b<2;b++){
        if(!V4) conv_load<8>(w,pp);
        conv_issue<48,8>(c,w,db,1,p.zero); wg_commit();
        pp+=512; db+=4;
        if(it && b==REDAT-2 && warp==0){ if(elect_one()){ bulk_wait0(); red_relaxed(p.s->cnt+EOFF); } __syncwarp(); }
        wg_wait<0>(); TSP(70+b+4*it,tid==0); }
      mbar_wait(wg==2? rxb : fb_+8*it,0,t0);
      if(GVP==1) asm volatile("{\n.reg .pred q;\nsetp.ne.b32 q, %2, 0;\n@q ld.relaxed.gpu.global.u32 %0, [%1];\n}":"+r"(xc):"l"(p.s->cnt+32+lane),"r"((int)(lead)):"memory");
      if(!V4) conv_load<3>(w,p3);
      conv_issue<32,3>(c,w,db+8,1,p.zero);
      { const uint64_t df=mkdesc(U+UB,128,FPL,0), dt3=mkdesc(TB+4928,256,128,0);
        #pragma unroll
        for(int k=0;k<4;k++) wgmma_n32_tn(c, df+k*8*(FPL/16), dt3+k*48, 1);
        wg_commit(); }
      TSP(5+4*it,tid==0);
      uint32_t gaw=__shfl_sync(~0u,gv,0);
      while(__any_sync(~0u,(gaw&0xffffu)!=tag16 && (int)(clk32()-t0)>=0)) gaw=ld_relaxed(p.s->mod+2*D_+chan(cta,ch));
      const float ga=bf_hi(gaw);
      wg_wait<0>(); reg_fence(c);
      TSP(6+4*it,tid==0);
      if(GVP==2) asm volatile("{\n.reg .pred q;\nsetp.ne.b32 q, %2, 0;\n@q ld.relaxed.gpu.global.u32 %0, [%1];\n}":"+r"(xc):"l"(p.s->cnt+32+lane),"r"((int)(lead)):"memory");
      float y[16];
      { const uint32_t xa=(it? kb : wg<2? sb+SM_KG2+14336+wg*7168 : sb+SM_FT)+(tl&63)*16;
        if(warp<2){
          #pragma unroll
          for(int i=0;i<4;i++) sts128f(xa+i*1024,make_float4(c[4*i],c[1+4*i],c[2+4*i],c[3+4*i]));
          #pragma unroll
          for(int i=0;i<16;i++) y[i]=c[16+i];
        } else {
          #pragma unroll
          for(int i=0;i<3;i++) sts128f(xa+(4+i)*1024,make_float4(c[20+4*i],c[21+4*i],c[22+4*i],c[23+4*i]));
          #pragma unroll
          for(int i=0;i<16;i++) y[i]=c[4+i];
        }
        bar_sync(1+wg,128);
        const uint32_t ya=xa+(warp<2? 4096:0);
        #pragma unroll
        for(int i=0;i<4;i++) if(i<3 || warp>=2){ float4 h=lds128f(ya+i*1024); y[4*i]+=h.x; y[4*i+1]+=h.y; y[4*i+2]+=h.z; y[4*i+3]+=h.w; } }
      { uint32_t o[8];
        #pragma unroll
        for(int i=0;i<8;i++){ uint32_t yb=pack_bf16(y[2*i],y[2*i+1]); o[i]=pack_bf16(ga*bf_lo(yb), ga*bf_hi(yb)); }
        const uint32_t lin=((warp>>1)*32+31-(lane>>4)*8-(lane&7))*64+(2*(warp&1)+((lane>>3)&1))*16;
        const uint32_t a=TB+(lin^(((lin>>7)&7)<<4));
        stsm4t(a,o[0],o[1],o[2],o[3]); stsm4t(a-1024,o[4],o[5],o[6],o[7]);
        fence_async_smem();
        if(it) bar_arrive(13+wg,160);
        else { bar_sync(1+wg,128);
          if(warp==0){ if((int)(__shfl_sync(~0u,xc,0)-(ep+1)*128)<0){ TSP(78,tid==0); flag_wait(p.s->cnt+32,(ep+1)*128,t0); }
            if(elect_one()){ fence_async_global(); tma_red2(&p.x1red,0,chan(cta,ch)*32,TB); bulk_commit(); } __syncwarp(); } }
      }
      TSP(7+4*it,tid==0); TSP(87,tid==256);
    }
    if(wid==8){ if(elect_one()){ bulk_wait0(); red_relaxed(p.s->cnt+EOFF); } __syncwarp(); }
    TSP(8,tid==0);
  } else {
    if(wsl>=0){
      mbar_wait(w1b,0,t0);
      TSP(19,lead);
      uint32_t a[80];
      #pragma unroll
      for(int k=0;k<10;k++){ uint32_t ad=sb+SM_WM+toff+k*1024;
        ldsm4t(ad+(((mi&1)^tsw)<<4),a[8*k],a[8*k+1],a[8*k+2],a[8*k+3]); ldsm4t(ad+(((2+(mi&1))^tsw)<<4),a[8*k+4],a[8*k+5],a[8*k+6],a[8*k+7]); }
      const uint32_t va=MI+1280+warp*32+16+t*4;
      { float s0[4], s1[4]; const uint64_t dv=mkdesc(MI+1280,128,256,0);
        wg_fence();
        #pragma unroll
        for(int k=0;k<10;k++){ const uint32_t* x=a+8*k; wgmma_n8_rs(s0,x[0],x[1],x[2],x[3],dv+k*16,k>0); wgmma_n8_rs(s1,x[4],x[5],x[6],x[7],dv+k*16,k>0); }
        wg_commit(); wg_wait<0>(); reg_fence(s0); reg_fence(s1);
        if(t==warp){ sts128f(MI+3840+warp*256+g*16,make_float4(s0[1],s0[3],s1[1],s1[3])); sts128f(MI+3968+warp*256+g*16,make_float4(s0[0],s0[2],s1[0],s1[2])); } }
      if(XRP==1){ if(warp==1){ if(elect_one()){ bulk_wait0(); red_relaxed(p.s->cnt+32); TS(18); } __syncwarp(); } }
      TSP(61,lead);
      bar_sync(4,128);
      uint32_t nm[4], cv[20];
      { float4 q=lds128f(MI+3840+t*256+g*16);
        #pragma unroll
        for(int k=0;k<2*CPF;k++) cv[k]=lds32(va+k*128);
        #pragma unroll
        for(int o=1;o<4;o<<=1){ q.x+=__shfl_xor_sync(~0u,q.x,o); q.y+=__shfl_xor_sync(~0u,q.y,o); q.z+=__shfl_xor_sync(~0u,q.z,o); q.w+=__shfl_xor_sync(~0u,q.w,o); }
        const float im=-1.f/D_; nm[0]=pack_bf16(q.x*im,q.x*im); nm[1]=pack_bf16(q.y*im,q.y*im); nm[2]=pack_bf16(q.z*im,q.z*im); nm[3]=pack_bf16(q.w*im,q.w*im); }
      const uint32_t oa=sb+SM_WM+(mi&1)*10240+(warp*20+(mi>>1))*128+(lane&7)*16;
      #pragma unroll
      for(int k=0;k<10;k++){ uint32_t y[8];
        #pragma unroll
        for(int i=0;i<8;i++) y[i]=bf2_fma(a[8*k+i],cv[2*k+((i>>1)&1)],nm[(i>>2)*2+(i&1)]);
        if(k==0){
          #pragma unroll
          for(int q=2*CPF;q<2*CPF+8 && q<20;q++) cv[q]=lds32(va+q*128); }
        if(k==2){
          #pragma unroll
          for(int q=2*CPF+8;q<20;q++) cv[q]=lds32(va+q*128); }
        stsm4t(oa+k*256,y[0],y[1],y[2],y[3]); stsm4t(oa+20480+k*256,y[4],y[5],y[6],y[7]); }
      TSP(85,lead);
      if(XRP==2){ if(warp==1){ if(elect_one()){ bulk_wait0(); red_relaxed(p.s->cnt+32); TS(18); } __syncwarp(); } }
      if(warp==0){ const uint32_t pa=MI+3968+(lane&7)*16+(lane>>3)*4;
        sts32f(MI+4864+lane*4, (mat?0.5f:1.f)*((lds32f(pa)+lds32f(pa+256))+(lds32f(pa+512)+lds32f(pa+768)))); }
      fence_async_smem();
      const int pc=sl*4+warp, su=pc/72, r=pc%72, jj= r<40? r/5 : (r-40)/4, ii= r<40? r%5 : 5+(r-40)%4;
      bar_sync(4,128);
      if(elect_one()){ tma_st2(&p.wps,(2*ii+mat)*64,(jj*3+su)*80,sb+SM_WM+warp*10240);
        if(warp==0) bulk_s2g(p.s->qs+mat*F_+sl*32,MI+4864,128);
        bulk_commit(); }
      __syncwarp();
    }
    #pragma unroll 1
    for(int i=0;i<2;i++) box_filter(sb+SM_KG+i*KG_WG+UF,tl);
    fence_async_smem();
    bar_sync(4,128);
    mbar_arrive_pred(fb_+8,1,lead); TSP(17,lead);
    if(elect_one()) bulk_wait0();
    __syncwarp();
    bar_sync(4,128);
    if(lead) red_relaxed(p.s->cnt+EOFF);
    TSP(20,lead);
  }
  int tile=cta;
  if(BYSM){ const int tp=cta>>1, d7=((tp-32)*37)>>8; tile=2*(tp<32? (tp&7)*8+(tp>>3) : tp<60? (tp-31-7*d7)*8+4+d7 : tp-56)+(cta&1); }
  const int m= MAPV==0? tile>>3 : MAPV==1? 4*(tile>>5)+((tile>>2)&3) : MAPV==2? 4*(tile>>5)+(tile&3) : MAPV==3? 2*(tile>>4)+(tile&1) : 4*(tile>>5)+((tile>>1)&3);
  const int j= MAPV==0? tile&7 : MAPV==1? ((tile>>2)&4)+(tile&3) : MAPV==2? ((tile>>2)&7) : MAPV==3? (tile>>1)&7 : ((tile>>2)&6)+(tile&1);
  if(wg>=2){
    asm volatile("setmaxnreg.dec.sync.aligned.u32 48;");
    if(wid==9 || wid==10){
      bar_sync(4+wid,160);
      if(elect_one()){ fence_async_global(); tma_red2(&p.x1red,0,chan(cta,wid-6)*32,sb+tb_off(wid-6)); bulk_commit();
        bulk_wait0_read(); mbar_arrive_pred(r1b,1,1); bulk_wait0(); red_relaxed(p.s->cnt); TS(89+wid); }
      __syncwarp(); }
    if(wid==8){ if(elect_one()){
      const unsigned char* wp=(const unsigned char*)p.s->Wp + (size_t)j*30*18432;
      TS(21);
      flag_wait(p.s->cnt+EOFF,(ep+1)*512,t0); fence_async_global();
      TS(22);
      int s=0, ph=1; int kc=0;
      #pragma unroll 1
      for(int i=0;i<30;i++){
        if(i==4){ mbar_wait(r1b,0,t0); TS(96); }
        if(i==6){ mbar_wait(prb+8,1,t0); fence_async_global(); TS(97); }
        mbar_wait(emptyb+8*s,ph,t0);
        if(OUTS && i>=OUTS && i<OUTE) mbar_wait(fullb+8*(s>=OUTS? s-OUTS : s+NSTG-OUTS),s>=OUTS? ph^1 : ph,t0);
        uint32_t st=sb+s*STG, fb=fullb+8*s;
        mbar_expect_tx(fb,STG);
        tma_ld2(st,&p.x1a,m*128,kc*64,fb);
        tma_ld2(st+8192,&p.x1a,m*128+64,kc*64,fb);
        bulk_g2s(st+16384,wp,18432,fb);
        wp+=18432; if(++kc==10) kc=0;
        if(++s==NSTG){s=0;ph^=1;}
      }
      const unsigned char* gp=(const unsigned char*)p.s->G+(size_t)m*27*16384; const unsigned char* w2=(const unsigned char*)p.s->W2p+(size_t)j*27*10240;
      uint32_t dep=emptyb+48; s=0; ph=0;
      #pragma unroll 1
      for(int i=0;i<27;i++){
        if(kc==0||kc==5){ mbar_wait(dep,0,t0); dep+= dep==emptyb+56? 16:8; fence_async_global(); }
        if(++kc==9) kc=0;
        if(i<NST2) mbar_wait(emptyb+8*(i-(i>3)),0,t0);
        else mbar_wait(empty2+8*s,ph,t0);
        uint32_t st=sb+s*STG2, fb=full2+8*s;
        mbar_expect_tx(fb,STG2);
        bulk_g2s(st+16384,w2,10240,fb);
        bulk_g2s(st,gp,16384,fb);
        if(i==RESAT){ mbar_expect_tx(resb,20480); tma_ld2(sb+SM_RES,&p.x1r,m*128,j*80,resb); tma_ld2(sb+SM_RES+10240,&p.x1r,m*128+64,j*80,resb); }
        gp+=16384; w2+=10240;
        if(++s==NST2){s=0; ph^=(i>=NST2);}
      }
    } }
    else if(wid==9){
      #pragma unroll 1
      for(int pt=0;pt<6;pt++){
        bar_sync((pt&1)? 5:11,160);
        if(elect_one()){
          const int kb0=(pt>>1)*72+((pt&1)? 40+j*4 : j*5);
          if(GSP==0) bulk_s2g((unsigned char*)p.s->G+(size_t)(m*216+kb0)*2048,sb+SM_GS+(pt&1)*10240,(5-(pt&1))*2048);
          else {
            #pragma unroll 1
            for(int q=0;q<5-(pt&1);q++){ bulk_s2g((unsigned char*)p.s->G+(size_t)(m*216+kb0+q)*2048,sb+SM_GS+(pt&1)*10240+q*2048,2048);
              if(GSP==1){ bulk_commit(); bulk_wait0_read(); } else __nanosleep(GSP); } }
          bulk_commit(); bulk_wait0_read(); mbar_arrive_pred(gsb,1,pt&1);
          bulk_wait0(); red_relaxed(p.s->gflag+m*32+pt); TS(62+pt);
        }
        __syncwarp();
      }
    }
    else if(wid==10){
      while(__any_sync(~0u,(int)(ld_relaxed(p.s->cnt+64)-(ep+1)*4)<0 && (int)(clk32()-t0)>=0)) __nanosleep(200);
      TSP(81,lane==0);
      const unsigned* gf=p.s->gflag+m*32+min(lane,5); const unsigned tgt=(ep+1)*8;
      int done=0; unsigned v[PDEPTH];
      #pragma unroll
      for(int k=0;k<PDEPTH;k++){ v[k]=ld_relaxed(gf); if(PDEPTH>1) __nanosleep(POLLNS); }
      while(done<6){
        #pragma unroll
        for(int k=0;k<PDEPTH;k++){
          const unsigned ok=__ballot_sync(~0u,(int)(v[k]-tgt)>=0 || (int)(clk32()-t0)<0);
          v[k]=ld_relaxed(gf);
          const int nd=__ffs(~ok|64)-1;
          mbar_arrive_pred(emptyb+48+8*lane+(lane>1? 8:0),1,lane>=done && lane<nd); TSP(23+lane,lane>=done && lane<nd);
          done=max(done,nd); } }
    }
    else if(wid==11){
      mbar_wait(r1b,0,t0);
      flag_wait(p.s->cnt,(ep+1)*256,t0); mbar_arrive_pred(prb+8,1,lane==0); TSP(77,lane==0);
      const unsigned* gbp=p.s->mod+5*D_+j*80; uint32_t a,b,c;
      while(true){ a=ld_relaxed(gbp+lane)^tag16; b=ld_relaxed(gbp+32+lane)^tag16; c=ld_relaxed(gbp+64+(lane&15))^tag16;
        if(!__any_sync(~0u,((a|b|c)&0xffffu) && (int)(clk32()-t0)>=0)) break;
        __nanosleep(200); }
      sts16(sb+SM_QS+2048+lane*2,a>>16); sts16(sb+SM_QS+2112+lane*2,b>>16); if(lane<16) sts16(sb+SM_QS+2176+lane*2,c>>16);
      bar_arrive(12,160);
    }
    else if(wg==3){
      const unsigned tag=ep+1;
      float su0=0,su1=0,sq0=0,sq1=0; float qa[2], qb[2];
      { const int row=warp*16+(lane>>4)*8+(lane&7);
        const uint32_t off=(j>>2)*8192+row*128+((((j&3)*2+((lane>>3)&1))^(lane&7))<<4);
        int s=0, ph=0;
        #pragma unroll 1
        for(int i=0;i<10;i++){
          mbar_wait(fullb+8*s,ph,t0);
          uint32_t a0,a1,a2,a3; ldsm4t(sb+s*STG+off,a0,a1,a2,a3);
          if(i==0){
            #pragma unroll
            for(int k=0;k<2;k++){ int q=min(tl+128*k,215); int r=q%72, f=(q/72)*576+(r<40? j*40+r : 280+j*32+r); qa[k]=__ldcg(p.s->qs+f); qb[k]=__ldcg(p.s->qs+F_+f); } }
          float x0=bf_lo(a0),x1=bf_hi(a0),x2=bf_lo(a2),x3=bf_hi(a2), y0=bf_lo(a1),y1=bf_hi(a1),y2=bf_lo(a3),y3=bf_hi(a3);
          __syncwarp();
          mbar_arrive_pred(emptyb+8*s,1,lane==0);
          su0+=(x0+x1)+(x2+x3); su1+=(y0+y1)+(y2+y3);
          sq0=fmaf(x0,x0,fmaf(x1,x1,fmaf(x2,x2,fmaf(x3,x3,sq0)))); sq1=fmaf(y0,y0,fmaf(y1,y1,fmaf(y2,y2,fmaf(y3,y3,sq1))));
          if(++s==NSTG){s=0;ph^=1;} } }
      { float a=(t&1)?sq0:su0, b=(t&1)?su0:sq0, c=(t&1)?sq1:su1, e=(t&1)?su1:sq1;
        a+=__shfl_xor_sync(~0u,b,1); c+=__shfl_xor_sync(~0u,e,1);
        float k=(t&2)?c:a, o=(t&2)?a:c; k+=__shfl_xor_sync(~0u,o,2);
        asm volatile("st.relaxed.gpu.global.b64 [%0], %1;"::"l"((unsigned long long*)(p.s->st2+warp*L_+m*128+j*16+(t>>1)*8+g)+(t&1)),
          "l"(((unsigned long long)tag<<32)|__float_as_uint(k)):"memory"); }
      TSP(80,lead);
      #pragma unroll
      for(int k=0;k<2;k++){ int q=tl+128*k; if(q<216) sts64f(sb+SM_QS+q*8,qa[k],qb[k]); }
      { unsigned long long a[4],b[4];
        while(true){ unsigned bad=0;
          __nanosleep(STNS);
          #pragma unroll
          for(int w=0;w<4;w++) asm volatile("ld.relaxed.gpu.global.v2.b64 {%0,%1}, [%2];":"=l"(a[w]),"=l"(b[w]):"l"(p.s->st2+w*L_+m*128+tl):"memory");
          #pragma unroll
          for(int w=0;w<4;w++) bad|=((unsigned)(a[w]>>32)^tag)|((unsigned)(b[w]>>32)^tag);
          if(!__any_sync(~0u,bad && (int)(clk32()-t0)>=0)) break; }
        const float su=(__uint_as_float((unsigned)a[0])+__uint_as_float((unsigned)a[1]))+(__uint_as_float((unsigned)a[2])+__uint_as_float((unsigned)a[3]));
        const float sq=(__uint_as_float((unsigned)b[0])+__uint_as_float((unsigned)b[1]))+(__uint_as_float((unsigned)b[2])+__uint_as_float((unsigned)b[3]));
        const float mu=su*(1.f/D_), rs=rsqrtf(fmaxf(sq*(1.f/D_)-mu*mu,0.f)+1e-5f);
        sts32f(sb+SM_ST+tl*4, rs); }
      bar_arrive(6,256); bar_arrive(7,256);
      TSP(29,lead);
    }
  } else {
    asm volatile("setmaxnreg.inc.sync.aligned.u32 208;");
    const uint32_t roff=(lane>>4)*1024+(lane&7)*128+(((2*warp+((lane>>3)&1))^(lane&7))<<4);
    #pragma unroll 1
    for(int sub=wg; sub<3; sub+=2){
      float acc0[72], acc1[72];
      int i0=sub*10; int s=i0%NSTG, ph=(i0/NSTG)&1, ps=0;
      const uint32_t rel= sub? 5:1;
      if(sub>0) bar_sync(7+sub,256);
      #pragma unroll 1
      for(int i=0;i<10;i++){
        mbar_wait(fullb+8*s,ph,t0);
        bar_arrive_pred(8+sub, 256, i==9);
        TSP(30+i0+i,lead);
        uint32_t st=sb+s*STG;
        uint64_t da=mkdesc(st,16,1024,1), db=mkdesc(st+16384,2304,128,0);
        wg_fence();
        #pragma unroll
        for(int kk=0;kk<4;kk++){
          wgmma_n144_tt(acc0, da+kk*128, db+kk*288, (i|kk)!=0);
          wgmma_n144_tt(acc1, da+512+kk*128, db+kk*288, (i|kk)!=0);
          if(kk==REL1){ wg_commit(); wg_wait<1>(); mbar_arrive_pred(emptyb+8*ps,rel,lead && i>0); }
        }
        if(REL1<3) wg_commit();
        ps=s; if(++s==NSTG){s=0;ph^=1;}
      }
      wg_wait<0>();
      reg_fence(acc0); reg_fence(acc1);
      mbar_arrive_pred(emptyb+8*ps,rel,lead);
      TSP(88+sub,lead);
      if(sub<2) bar_sync(6+sub,256);
      if(sub) mbar_wait(gsb,(sub-1)&1,t0);
      if(EPI==EPI2 || sub<2) geglu<EPI>(acc0,acc1,sb,sub,warp,lane,p.zero); else geglu<EPI2>(acc0,acc1,sb,sub,warp,lane,p.zero);
      fence_async_smem();
      bar_arrive(5,160);
      TSP(91+sub,lead);
    }
    if(wg==1){
      float acc0[40], acc1[40]; uint32_t res[40], gbw[10];
      int s=0, ph=0, ps=0;
      bar_sync(12,160);
      #pragma unroll
      for(int i=0;i<10;i++) gbw[i]=lds32(sb+SM_QS+2048+i*16+t*4);
      bar_sync(10,256);
      #pragma unroll 1
      for(int i=0;i<27;i++){
        mbar_wait(full2+8*s,ph,t0);
        TSP(100+i,lead && i<18);
        uint32_t st=sb+s*STG2;
        uint64_t da=mkdesc(st,2048,128,0), db=mkdesc(st+16384,1280,128,0);
        wg_fence();
        #pragma unroll
        for(int kk=0;kk<4;kk++){
          wgmma_n80_nt(acc0, da+kk*256, db+kk*160, (i|kk)!=0);
          wgmma_n80_nt(acc1, da+64+kk*256, db+kk*160, (i|kk)!=0);
          if(kk==REL2){ wg_commit(); wg_wait<1>(); mbar_arrive_pred(empty2+8*ps,1,lead && i>0); }
        }
        if(REL2<3) wg_commit();
        ps=s; if(++s==NST2){s=0;ph^=1;}
      }
      mbar_wait(resb,0,t0);
      #pragma unroll
      for(int k=0;k<10;k++) ldsm4t(sb+SM_RES+roff+(k/5)*10240+(k%5)*2048,res[4*k],res[4*k+1],res[4*k+2],res[4*k+3]);
      const uint32_t ob=sb+s*STG2+warp*2560;
      const uint32_t oa=ob+(lane&15)*160+(lane>>4)*16;
      wg_wait<0>();
      reg_fence(acc0); reg_fence(acc1);
      TSP(94,lead);
      #pragma unroll
      for(int h=0;h<2;h++){
        #pragma unroll
        for(int k=0;k<5;k++){ uint32_t o[4];
          #pragma unroll
          for(int r=0;r<4;r++){ const int a=8*k+2*r; o[r]=bf2_fma(h? pack_bf16(acc1[a],acc1[a+1]) : pack_bf16(acc0[a],acc0[a+1]), gbw[2*k+(r>>1)], res[20*h+4*k+r]); }
          stsm4(oa+h*10240+k*32,o[0],o[1],o[2],o[3]); }
        fence_async_smem();
        __syncwarp();
        if(elect_one()){ tma_st2(&p.out, j*80, m*128+h*64+warp*16, ob+h*10240); bulk_commit(); if(h) bulk_wait0_read(); }
        __syncwarp();
      }
      TSP(95,lead);
    }
  }
}

typedef CUresult (*EncFn)(CUtensorMap*, CUtensorMapDataType, cuuint32_t, void*, const cuuint64_t*, const cuuint64_t*, const cuuint32_t*, const cuuint32_t*, CUtensorMapInterleave, CUtensorMapSwizzle, CUtensorMapL2promotion, CUtensorMapFloatOOBfill);
static void mk2(EncFn enc, CUtensorMap* m, const void* p, cuuint64_t d0, cuuint64_t d1, cuuint64_t s1, cuuint32_t b0, cuuint32_t b1, CUtensorMapSwizzle sw, CUtensorMapL2promotion pr=CU_TENSOR_MAP_L2_PROMOTION_NONE){
  cuuint64_t gd[2]={d0,d1}, gs[1]={s1}; cuuint32_t bx[2]={b0,b1}, es[2]={1,1};
  CUresult r=enc(m,CU_TENSOR_MAP_DATA_TYPE_BFLOAT16,2,(void*)p,gd,gs,bx,es,CU_TENSOR_MAP_INTERLEAVE_NONE,sw,pr,CU_TENSOR_MAP_FLOAT_OOB_FILL_NONE);
  (void)r;
}
extern "C" void kernel_launch(void* const* d_in, const int* in_sizes, int n_in, void* d_out, int out_size){
  Params p;
  p.x=(const bf16*)d_in[0]; for(int i=0;i<6;i++) p.in[i]=(const bf16*)d_in[1+i];
  p.in[6]=p.in[7]=(const bf16*)d_in[11]; p.wgp=(const bf16*)d_in[8]; p.wup=(const bf16*)d_in[9]; p.wdp=(const bf16*)d_in[10];
  const bf16* wm=(const bf16*)d_in[12]; p.zero=0;
  EncFn enc=nullptr; cudaDriverEntryPointQueryResult qr;
  cudaGetDriverEntryPoint("cuTensorMapEncodeTiled",(void**)&enc,cudaEnableDefault,&qr);
  cudaGetSymbolAddress((void**)&p.s,g_scr); void *px1=p.s->x1T,*pin=p.s->inbox,*pwp=p.s->Wp;
  mk2(enc,&p.x1a,px1,L_,D_,L_*2,64,64,CU_TENSOR_MAP_SWIZZLE_128B);
  mk2(enc,&p.x1r,px1,L_,D_,L_*2,64,80,CU_TENSOR_MAP_SWIZZLE_128B);
  mk2(enc,&p.out,d_out,D_,L_,D_*2,80,16,CU_TENSOR_MAP_SWIZZLE_NONE);
  mk2(enc,&p.xts,px1,L_,D_,L_*2,16,160,CU_TENSOR_MAP_SWIZZLE_32B);
  mk2(enc,&p.xna,pin,128*80,128,128*160,48,128,CU_TENSOR_MAP_SWIZZLE_NONE);
  mk2(enc,&p.xnb,pin,128*80,128,128*160,32,128,CU_TENSOR_MAP_SWIZZLE_NONE);
  mk2(enc,&p.x1red,px1,64,D_*32,128,64,32,CU_TENSOR_MAP_SWIZZLE_128B);
  mk2(enc,&p.wm,wm,6*D_,D_,6*D_*2,32,160,CU_TENSOR_MAP_SWIZZLE_64B,PROMO);
  mk2(enc,&p.wg,p.wgp,F_,D_,F_*2,32,160,CU_TENSOR_MAP_SWIZZLE_64B,PROMO);
  mk2(enc,&p.wu,p.wup,F_,D_,F_*2,32,160,CU_TENSOR_MAP_SWIZZLE_64B,PROMO);
  mk2(enc,&p.wps,pwp,1152,24*80,2304,64,80,CU_TENSOR_MAP_SWIZZLE_NONE);
  int dev=0, nsm=0; cudaGetDevice(&dev); cudaDeviceGetAttribute(&nsm,cudaDevAttrMultiProcessorCount,dev);
  if(nsm==132){ cudaFuncSetAttribute(fused_kernel<true>,cudaFuncAttributeMaxDynamicSharedMemorySize,SM_ALLOC); fused_kernel<true><<<132,512,SM_ALLOC>>>(p); }
  else { cudaFuncSetAttribute(fused_kernel<false>,cudaFuncAttributeMaxDynamicSharedMemorySize,SM_ALLOC); fused_kernel<false><<<132,512,SM_ALLOC>>>(p); }
}
```
